```python
import torch

def _softmax(x, axis=-1):
    return torch.softmax(x, dim=axis)
def _gelu(x):
    return torch.nn.functional.gelu(x, approximate="tanh")
def _silu(x):
    return torch.nn.functional.silu(x)
def _sigmoid(x):
    return torch.sigmoid(x)
def _layernorm(x, axis=-1, eps=1e-5):
    m = x.mean(dim=axis, keepdim=True)
    v = x.var(dim=axis, keepdim=True, unbiased=False)
    return (x - m) / torch.sqrt(v + eps)
def _scatter_add(tgt, idx, src, axis=0):
    return tgt.clone().index_add_(axis, idx, src)
def _segment_sum(src, seg, n):
    out = torch.zeros((n,) + src.shape[1:], dtype=src.dtype)
    return out.index_add_(0, seg, src)
def _pad(x, pw):
    flat = tuple(v for pair in reversed(pw) for v in pair)
    return torch.nn.functional.pad(x, flat)

kernel_name = 'concat_heads__linear_kernel_hedgehog__ssm_conv_s5__prompt'

def setup_inputs():

    _w = (lambda a: (lambda t: t.to(torch.bfloat16) if t.is_floating_point() else t)(torch.as_tensor(a)))
    def _A_setup():
        B, S, D, H = 1, 2048, 576, 32
        Dh = D // H
        return {
            "x": _w((lambda *s: torch.randn(*s, dtype=torch.bfloat16) * 0.4)(B, S, D)),
            "wqkv": _w((lambda *s: torch.randn(*s, dtype=torch.bfloat16) * 0.4)(D, 3 * D)),
            "w_phi": _w((lambda *s: torch.randn(*s, dtype=torch.bfloat16) * 0.4)(H, Dh, Dh) * (Dh ** -0.5)),
            "wo": _w((lambda *s: torch.randn(*s, dtype=torch.bfloat16) * 0.05)(D, D)),
        }
    _A_in = _A_setup()

    def _B_setup():
        B, S, D = 1, 2048, 576
        P = D
        Lambda_re = -0.5 * (lambda _x: torch.exp(torch.as_tensor(_x)))((lambda *s: torch.randn(*s, dtype=torch.bfloat16) * 0.8)(P))
        Lambda_im = (lambda *s: torch.randn(*s, dtype=torch.bfloat16) * 0.8)(P) * 1.0
        B_re = (lambda *s: torch.randn(*s, dtype=torch.bfloat16) * 0.8)(P, D) * (D ** -0.5)
        B_im = (lambda *s: torch.randn(*s, dtype=torch.bfloat16) * 0.8)(P, D) * (D ** -0.5)
        C_re = (lambda *s: torch.randn(*s, dtype=torch.bfloat16) * 0.8)(D, P) * (P ** -0.5)
        C_im = (lambda *s: torch.randn(*s, dtype=torch.bfloat16) * 0.8)(D, P) * (P ** -0.5)
        log_dt = (lambda *s: torch.randn(*s, dtype=torch.bfloat16) * 0.8)(P) * 0.3 - 2.0
        Dskip = (lambda *s: torch.randn(*s, dtype=torch.bfloat16) * 0.8)(D)
        return {
            "x": _w((lambda *s: torch.randn(*s, dtype=torch.bfloat16) * 0.05)(B, S, D)),
            "Lambda_re": _w(Lambda_re),
            "Lambda_im": _w(Lambda_im),
            "B_re": _w(B_re),
            "B_im": _w(B_im),
            "C_re": _w(C_re),
            "C_im": _w(C_im),
            "log_dt": _w(log_dt),
            "Dskip": _w(Dskip),
        }
    _B_in = _B_setup()

    return {
        "A_x": _A_in["x"],
        "A_wqkv": _A_in["wqkv"],
        "A_w_phi": _A_in["w_phi"],
        "A_wo": _A_in["wo"],
        "B_x": _B_in["x"],
        "B_Lambda_re": _B_in["Lambda_re"],
        "B_Lambda_im": _B_in["Lambda_im"],
        "B_B_re": _B_in["B_re"],
        "B_B_im": _B_in["B_im"],
        "B_C_re": _B_in["C_re"],
        "B_C_im": _B_in["C_im"],
        "B_log_dt": _B_in["log_dt"],
        "B_Dskip": _B_in["Dskip"],
    }

def reference(A_x, A_wqkv, A_w_phi, A_wo, B_x, B_Lambda_re, B_Lambda_im, B_B_re, B_B_im, B_C_re, B_C_im, B_log_dt, B_Dskip):
    def _A_ref(x, wqkv, w_phi, wo):
        B, S, D = x.shape
        H = 32; Dh = D // H
        qkv = (lambda x, *d: x.permute(*d))((x @ wqkv).reshape(B, S, 3, H, Dh), 2, 0, 3, 1, 4)
        q, k, v = qkv[0], qkv[1], qkv[2]
        pq = torch.einsum("bhsd,hdf->bhsf", q, w_phi)
        pk = torch.einsum("bhsd,hdf->bhsf", k, w_phi)
        phi_q = torch.concatenate([_softmax(pq, axis=-1), _softmax(-pq, axis=-1)], axis=-1)
        phi_k = torch.concatenate([_softmax(pk, axis=-1), _softmax(-pk, axis=-1)], axis=-1)
        kv = torch.einsum("bhsf,bhsd->bhfd", phi_k, v)
        z  = torch.einsum("bhsf->bhf", phi_k)
        num = torch.einsum("bhqf,bhfd->bhqd", phi_q, kv)
        den = torch.einsum("bhqf,bhf->bhq", phi_q, z)[..., None] + 1e-6
        o = num / den
        return (lambda x, *d: x.permute(*d))(o, 0, 2, 1, 3).reshape(B, S, D) @ wo

    def _B_ref(x, Lambda_re, Lambda_im, B_re, B_im, C_re, C_im, log_dt, Dskip):
        Bsz, L, H = x.shape
        Lam = Lambda_re + 1j * Lambda_im
        Bmat = B_re + 1j * B_im
        Cmat = C_re + 1j * C_im
        dt = torch.exp(log_dt)
        Lam_bar = torch.exp(dt * Lam)
        B_bar = ((Lam_bar - 1.0) / Lam)[:, None] * Bmat
        Bu = torch.einsum("bld,pd->blp", x + 0j, B_bar)
        h = torch.zeros_like(Bu[:, 0, :])
        hs = []
        for t in range(L):
            h = Lam_bar[None, :] * h + Bu[:, t, :]
            hs.append(h)
        hseq = torch.stack(hs, 1)
        y = 2.0 * torch.einsum("blp,dp->bld", hseq, Cmat).real + x * Dskip[None, None, :]
        return y

    a = _A_ref(A_x, A_wqkv, A_w_phi, A_wo)
    b = _B_ref(B_x, B_Lambda_re, B_Lambda_im, B_B_re, B_B_im, B_C_re, B_C_im, B_log_dt, B_Dskip)
    return torch.concatenate([a, b], axis=-1)
```

```cpp
#include <cuda_runtime.h>
#include <cuda_bf16.h>
#include <stdint.h>
typedef __nv_bfloat16 bf16;
constexpr int S=2048, D=576;
__device__ float g_qkv[S*1728];
__device__ float g_phi[2][S*32*36];
__device__ float g_kv[32*36*19];
__device__ float g_o[S*D];
__device__ float g_bu[S*1152];
template<typename TA>
__global__ void gemm(const TA* A, int lda, const bf16* B, int sbk, int sbn, float* C, int ldc, int K, float alpha, int accum){
  __shared__ float As[16][65], Bs[16][65];
  int m0=blockIdx.y*64, n0=blockIdx.x*64, tx=threadIdx.x&15, ty=threadIdx.x>>4;
  float acc[4][4]={};
  for(int k0=0;k0<K;k0+=16){
    for(int i=threadIdx.x;i<1024;i+=256){ int r=i>>4,c=i&15; As[c][r]=(float)A[(size_t)(m0+r)*lda+k0+c]; }
    for(int i=threadIdx.x;i<1024;i+=256){ int c,r; if(sbk==1){r=i>>4;c=i&15;} else {c=i>>6;r=i&63;} Bs[c][r]=(float)B[(size_t)(k0+c)*sbk+(size_t)(n0+r)*sbn]; }
    __syncthreads();
    for(int k=0;k<16;k++){ for(int i=0;i<4;i++) for(int j=0;j<4;j++) acc[i][j]+=As[k][ty*4+i]*Bs[k][tx*4+j]; }
    __syncthreads();
  }
  for(int i=0;i<4;i++) for(int j=0;j<4;j++){ float* p=&C[(size_t)(m0+ty*4+i)*ldc+n0+tx*4+j]; *p = accum? *p+alpha*acc[i][j] : alpha*acc[i][j]; }
}
__global__ void phik(const bf16* wphi){
  int idx=blockIdx.x*blockDim.x+threadIdx.x; int h=idx&31, t=(idx>>5)&2047, ty=idx>>16;
  float p[18]; float mx=-1e30f,mn=1e30f;
  for(int f=0;f<18;f++){ float s=0; for(int d=0;d<18;d++) s+=g_qkv[t*1728+ty*576+h*18+d]*(float)wphi[h*324+d*18+f]; p[f]=s; mx=fmaxf(mx,s); mn=fminf(mn,s);}
  float s1=0,s2=0; for(int f=0;f<18;f++){ s1+=expf(p[f]-mx); s2+=expf(mn-p[f]); }
  for(int f=0;f<18;f++){ g_phi[ty][(t*32+h)*36+f]=expf(p[f]-mx)/s1; g_phi[ty][(t*32+h)*36+18+f]=expf(mn-p[f])/s2; }
}
__global__ void kvk(){ int h=blockIdx.x; int i=threadIdx.x; if(i>=36*19) return; int f=i/19,d=i%19; float s=0; for(int t=0;t<S;t++) s+=g_phi[1][(t*32+h)*36+f]*(d<18?g_qkv[t*1728+1152+h*18+d]:1.f); g_kv[h*684+i]=s; }
__global__ void ok(){ int idx=blockIdx.x*blockDim.x+threadIdx.x; int h=idx&31,t=idx>>5; float den=1e-6f; for(int f=0;f<36;f++) den+=g_phi[0][(t*32+h)*36+f]*g_kv[h*684+f*19+18];
  for(int d=0;d<18;d++){ float s=0; for(int f=0;f<36;f++) s+=g_phi[0][(t*32+h)*36+f]*g_kv[h*684+f*19+d]; g_o[t*D+h*18+d]=s/den; } }
__global__ void scan(const bf16* lre,const bf16* lim,const bf16* ldt){ int p=blockIdx.x*blockDim.x+threadIdx.x; if(p>=D) return;
  float dt=(float)__float2bfloat16(expf((float)ldt[p])); float a=(float)lre[p], b=(float)lim[p]; float e=expf(dt*a), Lr=e*cosf(dt*b), Li=e*sinf(dt*b);
  float den=a*a+b*b; float cr=((Lr-1)*a+Li*b)/den, ci=(Li*a-(Lr-1)*b)/den; float hr=0,hi=0;
  for(int t=0;t<S;t++){ float ur=g_bu[t*1152+p], ui=g_bu[t*1152+576+p]; float br=cr*ur-ci*ui, bi=cr*ui+ci*ur; float nr=Lr*hr-Li*hi+br, ni=Lr*hi+Li*hr+bi; hr=nr;hi=ni; g_bu[t*1152+p]=hr; g_bu[t*1152+576+p]=hi; } }
__global__ void skipk(const bf16* x,const bf16* ds,float* out){ int i=blockIdx.x*blockDim.x+threadIdx.x; int t=i/D,d=i%D; out[t*1152+576+d]+=(float)__float2bfloat16((float)x[i]*(float)ds[d]); }
extern "C" void kernel_launch(void* const* d_in, const int* in_sizes, int n_in, void* d_out, int out_size){
  const bf16* const* in=(const bf16* const*)d_in; float* out=(float*)d_out;
  float *qkv,*o,*bu; cudaGetSymbolAddress((void**)&qkv,g_qkv); cudaGetSymbolAddress((void**)&o,g_o); cudaGetSymbolAddress((void**)&bu,g_bu);
  gemm<bf16><<<dim3(27,32),256>>>(in[0],D,in[1],1728,1,qkv,1728,D,1.f,0);
  phik<<<512,256>>>(in[2]); kvk<<<32,704>>>(); ok<<<256,256>>>();
  gemm<float><<<dim3(9,32),256>>>(o,D,in[3],D,1,out,1152,D,1.f,0);
  gemm<bf16><<<dim3(9,32),256>>>(in[4],D,in[7],1,D,bu,1152,D,1.f,0);
  gemm<bf16><<<dim3(9,32),256>>>(in[4],D,in[8],1,D,bu+576,1152,D,1.f,0);
  scan<<<18,32>>>(in[5],in[6],in[11]);
  gemm<float><<<dim3(9,32),256>>>(bu,1152,in[9],1,D,out+576,1152,D,2.f,0);
  gemm<float><<<dim3(9,32),256>>>(bu+576,1152,in[10],1,D,out+576,1152,D,-2.f,1);
  skipk<<<S*D/256,256>>>(in[4],in[12],out);
}
```

```cpp
#include <cuda_runtime.h>
#include <cuda.h>
#include <cuda_bf16.h>
#include <stdint.h>

typedef __nv_bfloat16 bf16;

template <int N> struct WG;
template <> struct WG<72> {
  static __device__ __forceinline__ void ss(float (&d)[36], uint64_t da, uint64_t db, int scaleD) {
    asm volatile("{\n.reg .pred p;\nsetp.ne.b32 p, %38, 0;\n"
      "wgmma.mma_async.sync.aligned.m64n72k16.f32.bf16.bf16 {%0, %1, %2, %3, %4, %5, %6, %7, %8, %9, %10, %11, %12, %13, %14, %15, %16, %17, %18, %19, %20, %21, %22, %23, %24, %25, %26, %27, %28, %29, %30, %31, %32, %33, %34, %35}, %36, %37, p, 1, 1, 0, 0;\n}"
      : "+f"(d[0]), "+f"(d[1]), "+f"(d[2]), "+f"(d[3]), "+f"(d[4]), "+f"(d[5]), "+f"(d[6]), "+f"(d[7]), "+f"(d[8]), "+f"(d[9]), "+f"(d[10]), "+f"(d[11]), "+f"(d[12]), "+f"(d[13]), "+f"(d[14]), "+f"(d[15]), "+f"(d[16]), "+f"(d[17]), "+f"(d[18]), "+f"(d[19]), "+f"(d[20]), "+f"(d[21]), "+f"(d[22]), "+f"(d[23]), "+f"(d[24]), "+f"(d[25]), "+f"(d[26]), "+f"(d[27]), "+f"(d[28]), "+f"(d[29]), "+f"(d[30]), "+f"(d[31]), "+f"(d[32]), "+f"(d[33]), "+f"(d[34]), "+f"(d[35])
      : "l"(da), "l"(db), "r"(scaleD));
  }
};
template <> struct WG<144> {
  static __device__ __forceinline__ void ss(float (&d)[72], uint64_t da, uint64_t db, int scaleD) {
    asm volatile("{\n.reg .pred p;\nsetp.ne.b32 p, %74, 0;\n"
      "wgmma.mma_async.sync.aligned.m64n144k16.f32.bf16.bf16 {%0, %1, %2, %3, %4, %5, %6, %7, %8, %9, %10, %11, %12, %13, %14, %15, %16, %17, %18, %19, %20, %21, %22, %23, %24, %25, %26, %27, %28, %29, %30, %31, %32, %33, %34, %35, %36, %37, %38, %39, %40, %41, %42, %43, %44, %45, %46, %47, %48, %49, %50, %51, %52, %53, %54, %55, %56, %57, %58, %59, %60, %61, %62, %63, %64, %65, %66, %67, %68, %69, %70, %71}, %72, %73, p, 1, 1, 0, 0;\n}"
      : "+f"(d[0]), "+f"(d[1]), "+f"(d[2]), "+f"(d[3]), "+f"(d[4]), "+f"(d[5]), "+f"(d[6]), "+f"(d[7]), "+f"(d[8]), "+f"(d[9]), "+f"(d[10]), "+f"(d[11]), "+f"(d[12]), "+f"(d[13]), "+f"(d[14]), "+f"(d[15]), "+f"(d[16]), "+f"(d[17]), "+f"(d[18]), "+f"(d[19]), "+f"(d[20]), "+f"(d[21]), "+f"(d[22]), "+f"(d[23]), "+f"(d[24]), "+f"(d[25]), "+f"(d[26]), "+f"(d[27]), "+f"(d[28]), "+f"(d[29]), "+f"(d[30]), "+f"(d[31]), "+f"(d[32]), "+f"(d[33]), "+f"(d[34]), "+f"(d[35]), "+f"(d[36]), "+f"(d[37]), "+f"(d[38]), "+f"(d[39]), "+f"(d[40]), "+f"(d[41]), "+f"(d[42]), "+f"(d[43]), "+f"(d[44]), "+f"(d[45]), "+f"(d[46]), "+f"(d[47]), "+f"(d[48]), "+f"(d[49]), "+f"(d[50]), "+f"(d[51]), "+f"(d[52]), "+f"(d[53]), "+f"(d[54]), "+f"(d[55]), "+f"(d[56]), "+f"(d[57]), "+f"(d[58]), "+f"(d[59]), "+f"(d[60]), "+f"(d[61]), "+f"(d[62]), "+f"(d[63]), "+f"(d[64]), "+f"(d[65]), "+f"(d[66]), "+f"(d[67]), "+f"(d[68]), "+f"(d[69]), "+f"(d[70]), "+f"(d[71])
      : "l"(da), "l"(db), "r"(scaleD));
  }
};

constexpr int NA = 7, NB = 8;
constexpr int OFF_B   = NA * 16384;
constexpr int OFF_D   = OFF_B + NB * 9216;
constexpr int OFF_TAB = OFF_D + 36864;
constexpr int OFF_BAR = OFF_TAB + 5 * 576;
constexpr int OFF_TS  = OFF_BAR + 256;
constexpr int SMEM_BYTES = OFF_TS + 256 + 1024;
constexpr int BAR_FULL = 0, BAR_EMPTY = 64, BAR_W = 128, BAR_WO = 136, BAR_H = 144, BAR_O = 152, BAR_HRD = 160, BAR_ORD = 168;
constexpr float LOG2E = 1.4426950408889634f;

struct Maps { CUtensorMap xB, Bre, Bim, xA, W, hL, Cre, Cim, oL, woT, hS, oS, yS, aS; };
struct Ptrs { const bf16 *wqkv, *wphi, *wo, *xB, *lre, *lim, *ldt, *dskip; };

__device__ __align__(1024) bf16 g_W[8 * 216 * 576];
__device__ __align__(1024) bf16 g_woT[576 * 576];
__device__ __align__(1024) bf16 g_h[2048 * 1152];
__device__ __align__(1024) bf16 g_o[2048 * 576];
__device__ __align__(256) unsigned long long g_carry[16 * 576];
__device__ __align__(256) unsigned long long g_kvp[8 * 16 * 16 * 96];
__device__ __align__(256) unsigned long long g_kvt[8 * 1440];
__device__ __align__(256) unsigned g_cnt[64 * 32];
__device__ __align__(256) unsigned g_epoch[128 * 8];

__device__ __forceinline__ uint32_t smem_u32(const void* p) { return (uint32_t)__cvta_generic_to_shared(p); }
__device__ __forceinline__ void mbar_init(uint32_t bar, int cnt) { asm volatile("mbarrier.init.shared::cta.b64 [%0], %1;" ::"r"(bar), "r"(cnt) : "memory"); }
__device__ __forceinline__ void mbar_expect(uint32_t bar, int bytes) { asm volatile("mbarrier.arrive.expect_tx.shared::cta.b64 _, [%0], %1;" ::"r"(bar), "r"(bytes) : "memory"); }
__device__ __forceinline__ void mbar_arrive(uint32_t bar) { asm volatile("mbarrier.arrive.shared::cta.b64 _, [%0];" ::"r"(bar) : "memory"); }
__device__ __forceinline__ void mbar_wait(uint32_t bar, int parity) {
  asm volatile("{\n.reg .pred p;\n.reg .u32 c;\nmov.u32 c, 0;\nLAB_WAIT:\n"
               "mbarrier.try_wait.parity.shared::cta.b64 p, [%0], %1;\n@p bra DONE;\n"
               "add.u32 c, c, 1;\nsetp.lt.u32 p, c, 0x400000;\n@p bra LAB_WAIT;\ntrap;\nDONE:\n}" ::"r"(bar), "r"(parity) : "memory");
}
__device__ __forceinline__ bool elect_one() { uint32_t p; asm volatile("{\n.reg .pred P;\nelect.sync _|P, 0xffffffff;\nselp.u32 %0, 1, 0, P;\n}" : "=r"(p)); return p; }
__device__ __forceinline__ void tma2d(uint32_t dst, const CUtensorMap* tm, uint32_t bar, int x, int y) {
  asm volatile("cp.async.bulk.tensor.2d.shared::cluster.global.mbarrier::complete_tx::bytes [%0], [%1, {%3,%4}], [%2];" ::"r"(dst), "l"(tm), "r"(bar), "r"(x), "r"(y) : "memory"); }
__device__ __forceinline__ void tma5d(uint32_t dst, const CUtensorMap* tm, uint32_t bar, int x, int y) {
  asm volatile("cp.async.bulk.tensor.5d.shared::cluster.global.mbarrier::complete_tx::bytes [%0], [%1, {%3,0,0,%4,0}], [%2];" ::"r"(dst), "l"(tm), "r"(bar), "r"(x), "r"(y) : "memory"); }
__device__ __forceinline__ void tmast2d(const CUtensorMap* tm, uint32_t src, int x, int y) {
  asm volatile("cp.async.bulk.tensor.2d.global.shared::cta.bulk_group [%0, {%2,%3}], [%1];" ::"l"(tm), "r"(src), "r"(x), "r"(y) : "memory"); }
__device__ __forceinline__ void tmast5d(const CUtensorMap* tm, uint32_t src, int x, int y) {
  asm volatile("cp.async.bulk.tensor.5d.global.shared::cta.bulk_group [%0, {%2,0,0,%3,0}], [%1];" ::"l"(tm), "r"(src), "r"(x), "r"(y) : "memory"); }
__device__ __forceinline__ void bulk_commit() { asm volatile("cp.async.bulk.commit_group;" ::: "memory"); }
__device__ __forceinline__ void bulk_wait_read() { asm volatile("cp.async.bulk.wait_group.read 0;" ::: "memory"); }
__device__ __forceinline__ void bulk_wait() { asm volatile("cp.async.bulk.wait_group 0;" ::: "memory"); }
__device__ __forceinline__ void fence_async_smem() { asm volatile("fence.proxy.async.shared::cta;" ::: "memory"); }
__device__ __forceinline__ void pfdesc(const CUtensorMap* tm) { asm volatile("prefetch.tensormap [%0];" ::"l"(tm) : "memory"); }
__device__ __forceinline__ uint64_t mkdesc(uint32_t addr) { return (uint64_t)((addr & 0x3FFFF) >> 4) | ((uint64_t)1 << 16) | ((uint64_t)64 << 32) | ((uint64_t)1 << 62); }
template <int ID, int N> __device__ __forceinline__ void nb_sync() { asm volatile("bar.sync %0, %1;" ::"n"(ID), "n"(N) : "memory"); }
template <int ID, int N> __device__ __forceinline__ void nb_arrive() { asm volatile("bar.arrive %0, %1;" ::"n"(ID), "n"(N) : "memory"); }
__device__ __forceinline__ void cnt_add(unsigned* p) { asm volatile("red.release.gpu.global.add.u32 [%0], 1;" ::"l"(p) : "memory"); }
__device__ __forceinline__ void cnt_wait(const unsigned* p, unsigned target) {
  for (int it = 0; it < (1 << 20); it++) {
    unsigned v; asm volatile("ld.acquire.gpu.global.u32 %0, [%1];" : "=r"(v) : "l"(p) : "memory");
    if ((int)(v - target) >= 0) break;
  }
  asm volatile("fence.proxy.async.global;" ::: "memory");
}
__device__ __forceinline__ uint2 ld_ll(const unsigned long long* p) { unsigned long long v; asm volatile("ld.relaxed.gpu.global.u64 %0, [%1];" : "=l"(v) : "l"(p) : "memory"); return make_uint2((uint32_t)v, (uint32_t)(v >> 32)); }
__device__ __forceinline__ void st_ll(unsigned long long* p, uint32_t lo, uint32_t hi) { unsigned long long v = ((unsigned long long)hi << 32) | lo; asm volatile("st.relaxed.gpu.global.u64 [%0], %1;" ::"l"(p), "l"(v) : "memory"); }
__device__ __forceinline__ void st_ll2(unsigned long long* p, float a, float b, uint32_t tlo, uint32_t thi) { st_ll(p, (__float_as_uint(a) & ~15u) | tlo, (__float_as_uint(b) & ~15u) | thi); }
__device__ __forceinline__ uint32_t pack(float lo, float hi) { uint32_t r; asm("cvt.rn.bf16x2.f32 %0, %1, %2;" : "=r"(r) : "f"(hi), "f"(lo)); return r; }
__device__ __forceinline__ float ex2(float x) { float r; asm("ex2.approx.ftz.f32 %0, %1;" : "=f"(r) : "f"(x)); return r; }
__device__ __forceinline__ float rcp(float x) { float r; asm("rcp.approx.ftz.f32 %0, %1;" : "=f"(r) : "f"(x)); return r; }
__device__ __forceinline__ void sts128(uint32_t a, uint32_t x, uint32_t y, uint32_t z, uint32_t w) { asm volatile("st.shared.v4.u32 [%0], {%1,%2,%3,%4};" ::"r"(a), "r"(x), "r"(y), "r"(z), "r"(w) : "memory"); }
__device__ __forceinline__ void sts128f(uint32_t a, float x, float y, float z, float w) { asm volatile("st.shared.v4.f32 [%0], {%1,%2,%3,%4};" ::"r"(a), "f"(x), "f"(y), "f"(z), "f"(w) : "memory"); }
__device__ __forceinline__ void sts64f(uint32_t a, float x, float y) { asm volatile("st.shared.v2.f32 [%0], {%1,%2};" ::"r"(a), "f"(x), "f"(y) : "memory"); }
__device__ __forceinline__ void sts32(uint32_t a, uint32_t x) { asm volatile("st.shared.u32 [%0], %1;" ::"r"(a), "r"(x) : "memory"); }
__device__ __forceinline__ float4 lds128f(uint32_t a) { float4 v; asm volatile("ld.shared.v4.f32 {%0,%1,%2,%3}, [%4];" : "=f"(v.x), "=f"(v.y), "=f"(v.z), "=f"(v.w) : "r"(a) : "memory"); return v; }
__device__ __forceinline__ float2 lds64f(uint32_t a) { float2 v; asm volatile("ld.shared.v2.f32 {%0,%1}, [%2];" : "=f"(v.x), "=f"(v.y) : "r"(a) : "memory"); return v; }
__device__ __forceinline__ void ldsm4(uint32_t& a, uint32_t& b, uint32_t& c, uint32_t& d, uint32_t p) { asm volatile("ldmatrix.sync.aligned.m8n8.x4.shared.b16 {%0,%1,%2,%3}, [%4];" : "=r"(a), "=r"(b), "=r"(c), "=r"(d) : "r"(p) : "memory"); }
__device__ __forceinline__ void ldsm4t(uint32_t& a, uint32_t& b, uint32_t& c, uint32_t& d, uint32_t p) { asm volatile("ldmatrix.sync.aligned.m8n8.x4.trans.shared.b16 {%0,%1,%2,%3}, [%4];" : "=r"(a), "=r"(b), "=r"(c), "=r"(d) : "r"(p) : "memory"); }
__device__ __forceinline__ void ldsm2t(uint32_t& a, uint32_t& b, uint32_t p) { asm volatile("ldmatrix.sync.aligned.m8n8.x2.trans.shared.b16 {%0,%1}, [%2];" : "=r"(a), "=r"(b) : "r"(p) : "memory"); }
__device__ __forceinline__ void stsm4(uint32_t p, uint32_t a, uint32_t b, uint32_t c, uint32_t d) { asm volatile("stmatrix.sync.aligned.m8n8.x4.shared.b16 [%0], {%1,%2,%3,%4};" ::"r"(p), "r"(a), "r"(b), "r"(c), "r"(d) : "memory"); }
__device__ __forceinline__ void mma16(float (&c)[4], uint32_t a0, uint32_t a1, uint32_t a2, uint32_t a3, uint32_t b0, uint32_t b1) {
  asm("mma.sync.aligned.m16n8k16.row.col.f32.bf16.bf16.f32 {%0,%1,%2,%3}, {%4,%5,%6,%7}, {%8,%9}, {%0,%1,%2,%3};"
      : "+f"(c[0]), "+f"(c[1]), "+f"(c[2]), "+f"(c[3]) : "r"(a0), "r"(a1), "r"(a2), "r"(a3), "r"(b0), "r"(b1)); }
__device__ __forceinline__ void mma8(float (&c)[4], uint32_t a0, uint32_t a1, uint32_t b0) {
  asm("mma.sync.aligned.m16n8k8.row.col.f32.bf16.bf16.f32 {%0,%1,%2,%3}, {%4,%5}, {%6}, {%0,%1,%2,%3};"
      : "+f"(c[0]), "+f"(c[1]), "+f"(c[2]), "+f"(c[3]) : "r"(a0), "r"(a1), "r"(b0)); }
__device__ __forceinline__ uint32_t ldg32(const void* p) { return __ldg((const uint32_t*)p); }
__device__ __forceinline__ uint32_t ldg16x2(const bf16* p, int stride) { return (uint32_t)__ldg((const unsigned short*)p) | ((uint32_t)__ldg((const unsigned short*)(p + stride)) << 16); }
#define TS(i)

template <int N, int N0, int NK, int ORD>
__device__ __forceinline__ void mainloop(float (&acc)[2][N / 2], uint32_t base) {
  uint32_t sa = base + (N0 % NA) * 16384;
  uint32_t sb = base + OFF_B + ((N0 < 18 ? 2 * N0 : N0 + 18) % NB) * 9216;
  const uint32_t fb = base + OFF_BAR + BAR_FULL, eb = base + OFF_BAR + BAR_EMPTY;
#pragma unroll 1
  for (uint32_t n = N0; n < N0 + NK; n++) {
    mbar_wait(fb + 8 * (n & 7), (n >> 3) & 1);
    const uint64_t da = mkdesc(sa), db = mkdesc(sb);
    asm volatile("wgmma.fence.sync.aligned;" ::: "memory");
#pragma unroll
    for (int k = 0; k < 4; k++) {
      WG<N>::ss(acc[0], da + k * 2, db + k * 2, (n > N0 || k > 0));
      WG<N>::ss(acc[1], da + 512 + k * 2, db + k * 2, (n > N0 || k > 0));
    }
    asm volatile("wgmma.commit_group.sync.aligned;" ::: "memory");
    if (ORD && n == N0 + NK - 1) nb_arrive<ORD, 256>();
    asm volatile("wgmma.wait_group.sync.aligned 1;" ::: "memory");
    if (n > N0 && (threadIdx.x & 127) == 0) mbar_arrive(eb + 8 * ((n - 1) & 7));
    sa += 16384; if (sa == base + OFF_B) sa = base;
    sb += (N == 144 ? 18432 : 9216); if (sb == base + OFF_D) sb = base + OFF_B;
  }
  asm volatile("wgmma.wait_group.sync.aligned 0;" ::: "memory");
  if (N0 + NK < 54 && (threadIdx.x & 127) == 0) mbar_arrive(eb + 8 * ((N0 + NK - 1) & 7));
#pragma unroll
  for (int i = 0; i < 2; i++)
#pragma unroll
    for (int r = 0; r < N / 2; r++) asm volatile("" : "+f"(acc[i][r])::"memory");
}

__device__ __forceinline__ void dual_softmax(const float (&p)[18], uint32_t (&w)[18]) {
  float mx = p[0], mn = p[0];
#pragma unroll
  for (int f = 1; f < 18; f++) { mx = fmaxf(mx, p[f]); mn = fminf(mn, p[f]); }
  const float mxs = -mx * LOG2E, mns = mn * LOG2E;
  float a[18], b[18], sa0 = 0.f, sa1 = 0.f, sb0 = 0.f, sb1 = 0.f;
#pragma unroll
  for (int f = 0; f < 18; f++) { a[f] = ex2(fmaf(p[f], LOG2E, mxs)); b[f] = ex2(fmaf(p[f], -LOG2E, mns)); }
#pragma unroll
  for (int f = 0; f < 18; f += 2) { sa0 += a[f]; sa1 += a[f + 1]; sb0 += b[f]; sb1 += b[f + 1]; }
  const float ra = rcp(sa0 + sa1), rb = rcp(sb0 + sb1);
#pragma unroll
  for (int f = 0; f < 9; f++) { w[f] = pack(a[2 * f] * ra, a[2 * f + 1] * ra); w[9 + f] = pack(b[2 * f] * rb, b[2 * f + 1] * rb); }
}

__device__ __forceinline__ void fold_unit(const bf16* src, int ld, const bf16* wphi, bool fold, bf16* dst, bool perm, int lane) {
  const int g = lane >> 2, q = lane & 3;
  uint32_t B[4][4][3];
#pragma unroll
  for (int j = 0; j < 4; j++) {
    const bf16* p = src + (8 * (g >> 1) + 2 * j + (g & 1)) * ld + 2 * q;
#pragma unroll
    for (int h = 0; h < 4; h++) {
      B[h][j][0] = ldg32(p + 18 * h); B[h][j][1] = ldg32(p + 18 * h + 8);
      B[h][j][2] = q == 0 ? ldg32(p + 18 * h + 16) : 0u;
    }
  }
  uint32_t A[4][9];
  if (fold) {
#pragma unroll
    for (int h = 0; h < 4; h++) {
      const bf16* w = wphi + h * 324 + 36 * q + g;
      A[h][0] = ldg16x2(w, 18); A[h][1] = ldg16x2(w + 8, 18); A[h][2] = ldg16x2(w + 144, 18); A[h][3] = ldg16x2(w + 152, 18);
      A[h][4] = q == 0 ? ldg16x2(w + 288, 18) : 0u; A[h][5] = q == 0 ? ldg16x2(w + 296, 18) : 0u;
      A[h][6] = g < 2 ? ldg16x2(w + 16, 18) : 0u; A[h][7] = g < 2 ? ldg16x2(w + 160, 18) : 0u;
      A[h][8] = (g < 2 && q == 0) ? ldg16x2(w + 304, 18) : 0u;
    }
  } else {
    const uint32_t id = g == 2 * q ? 0x3F80u : (g == 2 * q + 1 ? 0x3F800000u : 0u);
#pragma unroll
    for (int h = 0; h < 4; h++) { A[h][0] = id; A[h][1] = 0; A[h][2] = 0; A[h][3] = id; A[h][4] = 0; A[h][5] = 0; A[h][6] = 0; A[h][7] = 0; A[h][8] = q == 0 ? id : 0u; }
  }
  const int r0 = perm ? 8 * (g >> 1) + (g & 1) : g, rs8 = perm ? 32 : 8, hs = perm ? 2 : 18;
#pragma unroll
  for (int h = 0; h < 4; h++) {
    uint32_t o0[4], o1[4], o2[4];
#pragma unroll
    for (int j = 0; j < 4; j++) {
      float c[4] = {0.f, 0.f, 0.f, 0.f}, d[4] = {0.f, 0.f, 0.f, 0.f};
      mma16(c, A[h][0], A[h][1], A[h][2], A[h][3], B[h][j][0], B[h][j][1]);
      mma8(c, A[h][4], A[h][5], B[h][j][2]);
      mma16(d, A[h][6], 0u, A[h][7], 0u, B[h][j][0], B[h][j][1]);
      mma8(d, A[h][8], 0u, B[h][j][2]);
      o0[j] = pack(c[0], c[1]); o1[j] = pack(c[2], c[3]); o2[j] = pack(d[0], d[1]);
    }
    bf16* dp = dst + (r0 + hs * h) * 576 + 8 * q;
    *(uint4*)dp = make_uint4(o0[0], o0[1], o0[2], o0[3]);
    *(uint4*)(dp + rs8 * 576) = make_uint4(o1[0], o1[1], o1[2], o1[3]);
    if (g < 2) *(uint4*)(dp + 2 * rs8 * 576) = make_uint4(o2[0], o2[1], o2[2], o2[3]);
  }
}

__global__ void __launch_bounds__(384, 1) fused_kernel(const __grid_constant__ Maps M, const __grid_constant__ Ptrs P) {
  extern __shared__ __align__(1024) uint8_t smem_raw[];
  uint32_t base = (smem_u32(smem_raw) + 1023) & ~1023u;
  asm volatile("mov.u32 %0, %0;" : "+r"(base));
  const int blk = blockIdx.x;
  if (blk == 112 || blk == 113 || blk >= 130) return;
  const int cta = blk > 113 ? blk - 2 : blk, tile = cta >> 3, grp = cta & 7;
  const int warp = __shfl_sync(0xffffffffu, threadIdx.x >> 5, 0), lane = threadIdx.x & 31;
  const uint32_t bars = base + OFF_BAR;
  if (warp == 8) {
    TS(0);
    if (elect_one()) {
      mbar_init(bars + BAR_FULL, 2);
      asm volatile("fence.mbarrier_init.release.cluster;" ::: "memory");
      mbar_expect(bars + BAR_FULL, 16384);
      tma5d(base, &M.xB, bars + BAR_FULL, 0, tile * 4);
      mbar_expect(bars + BAR_FULL, 18432);
      tma2d(base + OFF_B, &M.Bre, bars + BAR_FULL, 0, grp * 72);
      tma2d(base + OFF_B + 9216, &M.Bim, bars + BAR_FULL, 0, grp * 72);
    }
    TS(1);
  } else if (elect_one()) {
    if (warp < 8) { if (warp) mbar_init(bars + BAR_FULL + 8 * warp, 2); mbar_init(bars + BAR_EMPTY + 8 * warp, 1); }
    else { mbar_init(bars + BAR_W + 16 * (warp - 9), warp == 11 ? 4 : 1); mbar_init(bars + BAR_W + 8 + 16 * (warp - 9), warp == 11 ? 4 : 1); }
    asm volatile("fence.mbarrier_init.release.cluster;" ::: "memory");
  }
  __syncthreads();

  if (warp >= 8) {
    asm volatile("setmaxnreg.dec.sync.aligned.u32 40;");
    const uint32_t fb = bars + BAR_FULL, eb = bars + BAR_EMPTY;
    if (warp == 8) {
      uint32_t sa = base + 16384, n = 1;
      auto phase = [&](const CUtensorMap* tm, int k0, int k1, int row, bool five) {
#pragma unroll 1
        for (int k = k0; k < k1; k += 64) {
          if (n >= NA) mbar_wait(eb + 8 * ((n - NA) & 7), ((n - NA) >> 3) & 1);
          if (elect_one()) {
            const uint32_t bar = fb + 8 * (n & 7);
            mbar_expect(bar, 16384);
            if (five) tma5d(sa, tm, bar, k, row); else tma2d(sa, tm, bar, k, row);
          }
          n++; sa += 16384; if (sa == base + OFF_B) sa = base;
        }
      };
      phase(&M.xB, 64, 576, tile * 4, true);
      phase(&M.xA, 0, 576, tile * 128, false);
      phase(&M.xA, 0, 576, tile * 128, false);
      TS(2);
      mbar_wait(bars + BAR_H, 0);
      TS(3);
      phase(&M.hL, 0, 1152, tile * 128, false);
      TS(4);
      mbar_wait(bars + BAR_O, 0);
      TS(5);
      phase(&M.oL, 0, 576, tile * 128, false);
    } else if (warp == 9) {
      uint32_t sb = base + OFF_B + 18432, n = 1;
      auto phase2 = [&](const CUtensorMap* tm, const CUtensorMap* tm2, int k0, int row, int row2) {
#pragma unroll 1
        for (int k = k0; k < 576; k += 64) {
          if (n >= NB / 2) mbar_wait(eb + 8 * ((n - NB / 2) & 7), ((n - NB / 2) >> 3) & 1);
          if (elect_one()) {
            const uint32_t bar = fb + 8 * (n & 7);
            mbar_expect(bar, 18432);
            tma2d(sb, tm, bar, k, row); tma2d(sb + 9216, tm2, bar, k, row2);
          }
          n++; sb += 18432; if (sb == base + OFF_D) sb = base + OFF_B;
        }
      };
      auto phase1 = [&](const CUtensorMap* tm, int row) {
#pragma unroll 1
        for (int k = 0; k < 576; k += 64) {
          const uint32_t prev = n + 18 - NB, ps = prev < 36 ? prev >> 1 : prev - 18;
          mbar_wait(eb + 8 * (ps & 7), (ps >> 3) & 1);
          if (elect_one()) {
            const uint32_t bar = fb + 8 * (n & 7);
            mbar_expect(bar, 9216);
            tma2d(sb, tm, bar, k, row);
          }
          n++; sb += 9216; if (sb == base + OFF_D) sb = base + OFF_B;
        }
      };
      phase2(&M.Bre, &M.Bim, 64, grp * 72, grp * 72);
      TS(6);
      mbar_wait(bars + BAR_W, 0);
      TS(7);
      phase2(&M.W, &M.W, 0, grp * 216, grp * 216 + 72);
      phase1(&M.W, grp * 216 + 144);
      phase1(&M.Cre, grp * 72);
      phase1(&M.Cim, grp * 72);
      mbar_wait(bars + BAR_WO, 0);
      phase1(&M.woT, grp * 72);
    } else if (warp == 10) {
      if (elect_one()) {
        pfdesc(&M.xA); pfdesc(&M.W); pfdesc(&M.hS); pfdesc(&M.hL); pfdesc(&M.Cre); pfdesc(&M.Cim);
        pfdesc(&M.oS); pfdesc(&M.oL); pfdesc(&M.woT); pfdesc(&M.yS); pfdesc(&M.aS);
      }
    } else {
      if (lane == 0) {
        const unsigned ep = __ldcg(&g_epoch[cta * 8]) + 1;
        cnt_wait(&g_cnt[grp * 32], ep * 54);        mbar_arrive(bars + BAR_W);
        TS(8);
        cnt_wait(&g_cnt[(8 + grp) * 32], ep * 18);  mbar_arrive(bars + BAR_WO);
        cnt_wait(&g_cnt[(16 + tile) * 32], ep * 32); mbar_arrive(bars + BAR_H);
        TS(9);
        cnt_wait(&g_cnt[(32 + tile) * 32], ep * 32); mbar_arrive(bars + BAR_O);
        TS(10);
      }
    }
  } else {
    asm volatile("setmaxnreg.inc.sync.aligned.u32 232;");
    const int tid = threadIdx.x & 127, w = warp & 3, g = lane >> 2, q = lane & 3;
    const unsigned ep = __ldcg(&g_epoch[cta * 8]) + 1;
    const uint32_t tlo = ep & 15u, thi = (ep >> 4) & 15u;
    const uint32_t Dp = base + OFF_D, tab = base + OFF_TAB;
    if (warp < 4) {
      {
        float acc[2][72];
        mainloop<144, 0, 9, 1>(acc, base);
        TS(13);
        nb_sync<5, 256>();
#pragma unroll
        for (int j = 0; j < 9; j++) {
          const float4 L = lds128f(tab + (8 * j + 2 * q) * 8), C = lds128f(tab + 576 + (8 * j + 2 * q) * 8);
          float t[4];
#pragma unroll
          for (int e = 0; e < 2; e++) {
            const float lr = e ? L.z : L.x, li = e ? L.w : L.y, cr = e ? C.z : C.x, ci = e ? C.w : C.y;
            float tr = acc[0][4 * j + e], ti = acc[0][4 * (j + 9) + e];
#pragma unroll
            for (int s = 1; s < 4; s++) {
              const float ur = acc[s >> 1][4 * j + 2 * (s & 1) + e], ui = acc[s >> 1][4 * (j + 9) + 2 * (s & 1) + e];
              const float nr = fmaf(-li, ti, fmaf(lr, tr, ur)), ni = fmaf(li, tr, fmaf(lr, ti, ui));
              tr = nr; ti = ni;
            }
            t[2 * e] = fmaf(cr, tr, -ci * ti); t[2 * e + 1] = fmaf(-cr, ti, -ci * tr);
          }
          sts128f(Dp + (8 * w + g) * 576 + (8 * j + 2 * q) * 8, t[0], t[1], t[2], t[3]);
        }
        nb_sync<8, 128>();
        TS(14);
        float2 W4[4], L4, L32; uint2 cw[15];
        const unsigned long long* cp = &g_carry[grp * 72 + tid];
        if (tid < 72) {
          L4 = lds64f(tab + 2 * 576 + tid * 8); L32 = lds64f(tab + 3 * 576 + tid * 8);
#pragma unroll
          for (int c = 0; c < 4; c++) W4[c] = lds64f(Dp + (8 * c) * 576 + tid * 8);
#pragma unroll
          for (int s = 1; s < 8; s++)
#pragma unroll
            for (int c = 0; c < 4; c++) {
              const float2 t = lds64f(Dp + (8 * c + s) * 576 + tid * 8);
              const float nr = fmaf(-L4.y, W4[c].y, fmaf(L4.x, W4[c].x, t.x)), ni = fmaf(L4.y, W4[c].x, fmaf(L4.x, W4[c].y, t.y));
              W4[c].x = nr; W4[c].y = ni;
            }
          float tr = W4[0].x, ti = W4[0].y;
#pragma unroll
          for (int c = 1; c < 4; c++) { const float nr = fmaf(-L32.y, ti, fmaf(L32.x, tr, W4[c].x)), ni = fmaf(L32.y, tr, fmaf(L32.x, ti, W4[c].y)); tr = nr; ti = ni; }
          st_ll2(&g_carry[tile * 576 + grp * 72 + tid], tr, ti, tlo, thi);
#pragma unroll
          for (int t = 0; t < 15; t++) cw[t] = t < tile ? ld_ll(cp + t * 576) : make_uint2(tlo, thi);
        }
        TS(15);
#pragma unroll
        for (int j = 0; j < 9; j++) {
          const float4 C = lds128f(tab + 576 + (8 * j + 2 * q) * 8);
#pragma unroll
          for (int e = 0; e < 2; e++) {
            const float cr = e ? C.z : C.x, ci = e ? C.w : C.y;
#pragma unroll
            for (int s = 0; s < 4; s++) {
              float& ur = acc[s >> 1][4 * j + 2 * (s & 1) + e]; float& ui = acc[s >> 1][4 * (j + 9) + 2 * (s & 1) + e];
              const float nr = fmaf(cr, ur, -ci * ui), ni = fmaf(-cr, ui, -ci * ur);
              ur = nr; ui = ni;
            }
          }
        }
        if (tid < 72) {
          for (int it = 0; it < (1 << 20); it++) {
            uint32_t bad = 0;
#pragma unroll
            for (int t = 0; t < 15; t++) bad |= (cw[t].x ^ tlo) | (cw[t].y ^ thi);
            if ((bad & 15u) == 0) break;
#pragma unroll
            for (int t = 0; t < 15; t++) if (t < tile) cw[t] = ld_ll(cp + t * 576);
          }
          TS(16);
          const float2 L128 = lds64f(tab + 4 * 576 + tid * 8);
          float hr = 0.f, hi = 0.f;
#pragma unroll
          for (int t = 0; t < 15; t++) if (t < tile) {
            const float nr = fmaf(-L128.y, hi, fmaf(L128.x, hr, __uint_as_float(cw[t].x))), ni = fmaf(L128.y, hr, fmaf(L128.x, hi, __uint_as_float(cw[t].y)));
            hr = nr; hi = ni;
          }
          float2 Pf[4]; Pf[0] = make_float2(hr, hi);
#pragma unroll
          for (int c = 1; c < 4; c++) Pf[c] = make_float2(fmaf(-L32.y, Pf[c - 1].y, fmaf(L32.x, Pf[c - 1].x, W4[c - 1].x)), fmaf(L32.y, Pf[c - 1].x, fmaf(L32.x, Pf[c - 1].y, W4[c - 1].y)));
#pragma unroll
          for (int s = 0; s < 8; s++)
#pragma unroll
            for (int c = 0; c < 4; c++) {
              const uint32_t a = Dp + (8 * c + s) * 576 + tid * 8;
              const float2 t = lds64f(a);
              sts64f(a, Pf[c].x, Pf[c].y);
              const float nr = fmaf(-L4.y, Pf[c].y, fmaf(L4.x, Pf[c].x, t.x)), ni = fmaf(L4.y, Pf[c].x, fmaf(L4.x, Pf[c].y, t.y));
              Pf[c].x = nr; Pf[c].y = ni;
            }
        }
        nb_sync<8, 128>();
        TS(17);
        uint32_t hp[18][4];
#pragma unroll
        for (int j = 0; j < 9; j++) {
          const float4 L = lds128f(tab + (8 * j + 2 * q) * 8), H = lds128f(Dp + (8 * w + g) * 576 + (8 * j + 2 * q) * 8);
          float r0 = H.x, i0 = H.y, r1 = H.z, i1 = H.w;
#pragma unroll
          for (int s = 0; s < 4; s++) {
            const int ir = 4 * j + 2 * (s & 1), ii = ir + 36;
            const float nr0 = fmaf(L.y, i0, fmaf(L.x, r0, acc[s >> 1][ir])), ni0 = fmaf(-L.y, r0, fmaf(L.x, i0, acc[s >> 1][ii]));
            const float nr1 = fmaf(L.w, i1, fmaf(L.z, r1, acc[s >> 1][ir + 1])), ni1 = fmaf(-L.w, r1, fmaf(L.z, i1, acc[s >> 1][ii + 1]));
            r0 = nr0; i0 = ni0; r1 = nr1; i1 = ni1;
            hp[j][s] = pack(r0, r1); hp[9 + j][s] = pack(i0, i1);
          }
        }
        nb_sync<8, 128>();
        const uint32_t hs = Dp + w * 9216, ha = hs + (lane >> 4) * 2304 + (lane & 15) * 144;
#pragma unroll
        for (int j = 0; j < 18; j++) stsm4(ha + (j / 9) * 4608 + (j % 9) * 16, hp[j][0], hp[j][1], hp[j][2], hp[j][3]);
        fence_async_smem();
        __syncwarp();
        TS(18);
        if (lane == 0) {
          const int r = tile * 128 + 16 * w;
          tmast2d(&M.hS, hs, grp * 72, r); tmast2d(&M.hS, hs + 2304, grp * 72, r + 64);
          tmast2d(&M.hS, hs + 4608, 576 + grp * 72, r); tmast2d(&M.hS, hs + 6912, 576 + grp * 72, r + 64);
          bulk_commit(); bulk_wait_read(); mbar_arrive(bars + BAR_HRD);
          bulk_wait(); cnt_add(&g_cnt[(16 + tile) * 32]);
        }
        __syncwarp();
        TS(19);
      }
      nb_sync<2, 256>();
      TS(20);
      {
        uint32_t af[2][4][10];
        {
          float acc[2][36];
          mainloop<72, 18, 9, 3>(acc, base);
          TS(21);
          nb_sync<6, 256>();
          const uint32_t ws = Dp + w * 5248;
          if (tid < 48) sts128(Dp + 20992 + (tid / 12) * 1920 + 36 * 48 + (tid % 12) * 16, 0, 0, 0, 0);
#pragma unroll
          for (int b = 0; b < 2; b++) {
#pragma unroll
            for (int i = 0; i < 2; i++) {
              float p[18]; uint32_t ph[18];
#pragma unroll
              for (int f = 0; f < 18; f++) p[f] = acc[b][4 * (f >> 1) + 2 * i + (f & 1)];
              dual_softmax(p, ph);
              const uint32_t a = ws + q * 1312 + (8 * i + g) * 80;
#pragma unroll
              for (int c = 0; c < 4; c++) sts128(a + 16 * c, ph[4 * c], ph[4 * c + 1], ph[4 * c + 2], ph[4 * c + 3]);
              sts128(a + 64, ph[16], ph[17], 0, 0);
            }
            __syncwarp();
            const uint32_t la = ws + (lane & 15) * 80 + (lane >> 4) * 16, lb = ws + (lane >> 4) * 1312 + (lane & 15) * 80 + 64;
#pragma unroll
            for (int h = 0; h < 4; h++) {
              ldsm4(af[b][h][0], af[b][h][1], af[b][h][2], af[b][h][3], la + h * 1312);
              ldsm4(af[b][h][4], af[b][h][5], af[b][h][6], af[b][h][7], la + h * 1312 + 32);
            }
            ldsm4(af[b][0][8], af[b][0][9], af[b][1][8], af[b][1][9], lb);
            ldsm4(af[b][2][8], af[b][2][9], af[b][3][8], af[b][3][9], lb + 2624);
            __syncwarp();
          }
        }
        TS(22);
        if (tid < 120) {
          const unsigned long long* kp = &g_kvt[grp * 1440 + tid];
          uint2 kw[12];
          for (int it = 0; it < (1 << 20); it++) {
            uint32_t bad = 0;
#pragma unroll
            for (int m = 0; m < 12; m++) kw[m] = ld_ll(kp + 120 * m);
#pragma unroll
            for (int m = 0; m < 12; m++) bad |= kw[m].y ^ ep;
            if (bad == 0) break;
          }
          const int u = tid % 10, r0 = tid / 10;
          const uint32_t a = Dp + 20992 + r0 * 48 + (u < 9 ? 12 * (u % 3) + 4 * (u / 3) : 36);
#pragma unroll
          for (int m = 0; m < 12; m++) sts32(a + (m / 3) * 1920 + (m % 3) * 576, kw[m].x);
        }
        nb_sync<8, 128>();
        TS(23);
        const uint32_t os = Dp + w * 5248, tb = Dp + 20992 + lane * 48, tb2 = Dp + 20992 + (32 + (lane & 7)) * 48 + ((lane >> 3) % 3) * 16;
#pragma unroll
        for (int h = 0; h < 4; h++) {
          uint32_t bf[3][4], bk[4];
#pragma unroll
          for (int j = 0; j < 3; j++) ldsm4t(bf[j][0], bf[j][1], bf[j][2], bf[j][3], tb + h * 1920 + 16 * j);
          ldsm4t(bk[0], bk[1], bk[2], bk[3], tb2 + h * 1920);
#pragma unroll
          for (int b = 0; b < 2; b++) {
            float c[3][4];
#pragma unroll
            for (int j = 0; j < 3; j++) {
              c[j][0] = c[j][1] = c[j][2] = c[j][3] = 0.f;
              mma16(c[j], af[b][h][0], af[b][h][1], af[b][h][2], af[b][h][3], bf[j][0], bf[j][1]);
              mma16(c[j], af[b][h][4], af[b][h][5], af[b][h][6], af[b][h][7], bf[j][2], bf[j][3]);
              mma8(c[j], af[b][h][8], af[b][h][9], bk[j]);
            }
            const float d0 = rcp(__shfl_sync(0xffffffffu, c[2][0], (lane & ~3) | 1) + 1e-6f);
            const float d1 = rcp(__shfl_sync(0xffffffffu, c[2][2], (lane & ~3) | 1) + 1e-6f);
            const uint32_t a = os + b * 2304 + g * 144 + h * 36 + q * 4;
            sts32(a, pack(c[0][0] * d0, c[0][1] * d0)); sts32(a + 16, pack(c[1][0] * d0, c[1][1] * d0));
            sts32(a + 1152, pack(c[0][2] * d1, c[0][3] * d1)); sts32(a + 1168, pack(c[1][2] * d1, c[1][3] * d1));
            if (q == 0) { sts32(a + 32, pack(c[2][0] * d0, c[2][1] * d0)); sts32(a + 1184, pack(c[2][2] * d1, c[2][3] * d1)); }
          }
        }
        fence_async_smem();
        __syncwarp();
        TS(24);
        if (lane == 0) {
          const int r = tile * 128 + 16 * w;
          tmast2d(&M.oS, os, grp * 72, r); tmast2d(&M.oS, os + 2304, grp * 72, r + 64);
          bulk_commit(); bulk_wait_read(); mbar_arrive(bars + BAR_ORD);
          bulk_wait(); cnt_add(&g_cnt[(32 + tile) * 32]);
        }
        __syncwarp();
        TS(25);
      }
      nb_sync<4, 256>();
      TS(26);
      {
        float acc[2][36];
        mainloop<72, 45, 9, 0>(acc, base);
        TS(27);
        const uint32_t st = base + w * 9216, a = st + g * 288 + q * 8;
#pragma unroll
        for (int b = 0; b < 2; b++)
#pragma unroll
          for (int j = 0; j < 9; j++) {
            sts64f(a + b * 4608 + j * 32, acc[b][4 * j], acc[b][4 * j + 1]);
            sts64f(a + b * 4608 + 2304 + j * 32, acc[b][4 * j + 2], acc[b][4 * j + 3]);
          }
        fence_async_smem();
        __syncwarp();
        if (lane == 0) {
          const int r = tile * 128 + 16 * w;
          tmast2d(&M.aS, st, grp * 72, r); tmast2d(&M.aS, st + 4608, grp * 72, r + 64);
          bulk_commit();
          if (w == 0) g_epoch[cta * 8] = ep;
          bulk_wait_read();
        }
        TS(28);
      }
    } else {
      {
        float lre = 0.f, lim = 0.f, ldt = 0.f;
        if (tid < 72) { lre = __bfloat162float(P.lre[grp * 72 + tid]); lim = __bfloat162float(P.lim[grp * 72 + tid]); ldt = __bfloat162float(P.ldt[grp * 72 + tid]); }
        const int wid = cta * 4 + w;
#pragma unroll 1
        for (int u = wid; u < 576; u += 512) {
          if (u < 432) {
            const int ug = u / 54, r = u - 54 * ug, ty = r / 18, kc = r - 18 * ty;
            fold_unit(P.wqkv + kc * 32 * 1728 + (ty == 2 ? 0 : ty + 1) * 576 + 72 * ug, 1728, P.wphi + ug * 4 * 324, ty != 1,
                      g_W + (ug * 216 + ty * 72) * 576 + 32 * kc, true, lane);
            __syncwarp();
            if (lane == 0) cnt_add(&g_cnt[ug * 32]);
          } else {
            const int r = u - 432, ug = r / 18, kc = r - 18 * ug;
            fold_unit(P.wo + kc * 32 * 576 + 72 * ug, 576, P.wphi, false, g_woT + ug * 72 * 576 + 32 * kc, false, lane);
            __syncwarp();
            if (lane == 0) cnt_add(&g_cnt[(8 + ug) * 32]);
          }
        }
        TS(32);
        if (tid < 72) {
          const float dt = __bfloat162float(__float2bfloat16(expf(ldt)));
          const float e = expf(dt * lre); float sn, cs; sincosf(dt * lim, &sn, &cs);
          float lr = e * cs, li = e * sn;
          const float den = lre * lre + lim * lim, nr = lr - 1.f;
          sts64f(tab + tid * 8, lr, li);
          sts64f(tab + 576 + tid * 8, 2.f * (nr * lre + li * lim) / den, 2.f * (li * lre - nr * lim) / den);
          li = -li;
#pragma unroll
          for (int s = 1; s <= 7; s++) {
            const float t = lr * lr - li * li; li = 2.f * lr * li; lr = t;
            if (s == 2) sts64f(tab + 2 * 576 + tid * 8, lr, li);
            if (s == 5) sts64f(tab + 3 * 576 + tid * 8, lr, li);
            if (s == 7) sts64f(tab + 4 * 576 + tid * 8, lr, li);
          }
        }
        nb_arrive<5, 256>();
        TS(33);
      }
      nb_sync<1, 256>();
      TS(34);
      {
        float acc[2][72];
        mainloop<144, 9, 9, 2>(acc, base);
        TS(35);
        mbar_wait(bars + BAR_HRD, 0);
        float kv[3][3][4];
#pragma unroll
        for (int m = 0; m < 3; m++)
#pragma unroll
          for (int j = 0; j < 3; j++) kv[m][j][0] = kv[m][j][1] = kv[m][j][2] = kv[m][j][3] = 0.f;
#pragma unroll
        for (int b = 0; b < 2; b++) {
          uint32_t ph[2][18];
#pragma unroll
          for (int i = 0; i < 2; i++) {
            float p[18];
#pragma unroll
            for (int f = 0; f < 18; f++) p[f] = acc[b][4 * (f >> 1) + 2 * i + (f & 1)];
            dual_softmax(p, ph[i]);
          }
          if (b) nb_sync<9, 128>();
#pragma unroll
          for (int i = 0; i < 2; i++) {
            uint32_t v[9];
#pragma unroll
            for (int d = 0; d < 9; d++) v[d] = pack(acc[b][36 + 4 * d + 2 * i], acc[b][36 + 4 * d + 2 * i + 1]);
            const uint32_t a = Dp + q * 7200 + (16 * w + 8 * i + g) * 112;
            sts128(a, v[0], v[1], v[2], 0x00003F80u);
            sts128(a + 16, v[3], v[4], v[5], ph[i][0]);
            sts128(a + 32, v[6], v[7], v[8], ph[i][1]);
#pragma unroll
            for (int c = 0; c < 4; c++) sts128(a + 48 + 16 * c, ph[i][2 + 4 * c], ph[i][3 + 4 * c], ph[i][4 + 4 * c], ph[i][5 + 4 * c]);
          }
          nb_sync<9, 128>();
          const uint32_t la = Dp + w * 7200 + ((lane & 7) + 8 * (lane >> 4)) * 112 + 16 + ((lane >> 3) & 1) * 16;
          const uint32_t l0 = Dp + w * 7200 + lane * 112;
#pragma unroll
          for (int k2 = 0; k2 < 2; k2++) {
            uint32_t c0[4];
            ldsm4t(c0[0], c0[1], c0[2], c0[3], l0 + k2 * 32 * 112);
#pragma unroll
            for (int kk = 0; kk < 2; kk++) {
              uint32_t a[3][4];
#pragma unroll
              for (int m = 0; m < 3; m++) ldsm4t(a[m][0], a[m][1], a[m][2], a[m][3], la + (2 * k2 + kk) * 16 * 112 + 32 * m);
#pragma unroll
              for (int m = 0; m < 3; m++) {
                mma16(kv[m][0], a[m][0], a[m][1], a[m][2], a[m][3], c0[2 * kk], c0[2 * kk + 1]);
                mma16(kv[m][1], a[m][0], a[m][1], a[m][2], a[m][3], a[0][0], a[0][2]);
                mma16(kv[m][2], a[m][0], a[m][1], a[m][2], a[m][3], a[0][1], a[0][3]);
              }
            }
          }
        }
        nb_arrive<6, 256>();
        TS(36);
#pragma unroll
        for (int m = 0; m < 3; m++)
#pragma unroll
          for (int hf = 0; hf < 2; hf++) {
            const int f = m == 0 ? 2 * hf + g - 6 : 16 * m - 12 + 8 * hf + g;
            if (m > 0 || g >= 6) {
              const int sl = f / 9;
              unsigned long long* pp = &g_kvp[((grp * 16 + 4 * w + sl) * 16 + tile) * 96 + (f - 9 * sl) * 10 + 3 * q];
              st_ll2(pp, kv[m][0][2 * hf], kv[m][0][2 * hf + 1], tlo, thi);
              if (q < 3) { st_ll2(pp + 1, kv[m][1][2 * hf], kv[m][1][2 * hf + 1], tlo, thi); st_ll2(pp + 2, kv[m][2][2 * hf], kv[m][2][2 * hf + 1], tlo, thi); }
            }
          }
        TS(37);
        if (tid < 90) {
          const unsigned long long* pp = &g_kvp[(grp * 16 + tile) * 16 * 96 + tid];
          uint2 kw[16];
          for (int it = 0; it < (1 << 20); it++) {
            uint32_t bad = 0;
#pragma unroll
            for (int t = 0; t < 16; t++) kw[t] = ld_ll(pp + t * 96);
#pragma unroll
            for (int t = 0; t < 16; t++) bad |= (kw[t].x ^ tlo) | (kw[t].y ^ thi);
            if ((bad & 15u) == 0) break;
          }
          float s0 = 0.f, s1 = 0.f;
#pragma unroll
          for (int t = 0; t < 16; t++) { s0 += __uint_as_float(kw[t].x); s1 += __uint_as_float(kw[t].y); }
          if (tid % 10 == 9) s1 = 0.f;
          st_ll(&g_kvt[grp * 1440 + tile * 90 + tid], pack(s0, s1), ep);
        }
        TS(38);
      }
      {
        uint32_t xs[2][2][9], ds[9];
        const bf16* xp = P.xB + (size_t)(tile * 128 + 32 * w + 4 * g) * 576 + grp * 72 + 2 * q;
#pragma unroll
        for (int j = 0; j < 9; j++) {
          ds[j] = ldg32(P.dskip + grp * 72 + 8 * j + 2 * q);
#pragma unroll
          for (int s = 0; s < 4; s++) xs[s >> 1][s & 1][j] = ldg32(xp + s * 576 + 8 * j);
        }
        nb_sync<3, 256>();
        TS(39);
        float acc[2][36];
        mainloop<72, 27, 18, 4>(acc, base);
        TS(40);
        mbar_wait(bars + BAR_ORD, 0);
        const uint32_t st = Dp + w * 9216, a = st + g * 288 + q * 8;
#pragma unroll
        for (int b = 0; b < 2; b++)
#pragma unroll
          for (int i = 0; i < 2; i++)
#pragma unroll
            for (int j = 0; j < 9; j++) {
              const __nv_bfloat162 sk = __hmul2(*(const __nv_bfloat162*)&xs[b][i][j], *(const __nv_bfloat162*)&ds[j]);
              sts64f(a + b * 4608 + i * 2304 + j * 32, acc[b][4 * j + 2 * i] + __low2float(sk), acc[b][4 * j + 2 * i + 1] + __high2float(sk));
            }
        fence_async_smem();
        __syncwarp();
        if (lane == 0) { tmast5d(&M.yS, st, 576 + grp * 72, tile * 4 + w); bulk_commit(); bulk_wait_read(); }
        TS(41);
      }
    }
  }
}

typedef CUresult (*EncFn)(CUtensorMap*, CUtensorMapDataType, cuuint32_t, void*, const cuuint64_t*, const cuuint64_t*, const cuuint32_t*,
                          const cuuint32_t*, CUtensorMapInterleave, CUtensorMapSwizzle, CUtensorMapL2promotion, CUtensorMapFloatOOBfill);

static void mk2(EncFn enc, CUtensorMap* m, const void* p, int esz, int cols, int rows, int bc, int br, bool swz) {
  cuuint64_t gd[2] = {(cuuint64_t)cols, (cuuint64_t)rows}, gs[1] = {(cuuint64_t)cols * esz};
  cuuint32_t bd[2] = {(cuuint32_t)bc, (cuuint32_t)br}, es[2] = {1, 1};
  enc(m, esz == 2 ? CU_TENSOR_MAP_DATA_TYPE_BFLOAT16 : CU_TENSOR_MAP_DATA_TYPE_FLOAT32, 2, (void*)p, gd, gs, bd, es, CU_TENSOR_MAP_INTERLEAVE_NONE,
      swz ? CU_TENSOR_MAP_SWIZZLE_128B : CU_TENSOR_MAP_SWIZZLE_NONE, CU_TENSOR_MAP_L2_PROMOTION_L2_128B, CU_TENSOR_MAP_FLOAT_OOB_FILL_NONE);
}
static void mk5(EncFn enc, CUtensorMap* m, const void* p, int esz, int cols, int bc, int bw, bool swz) {
  const cuuint64_t rb = (cuuint64_t)cols * esz;
  cuuint64_t gd[5] = {(cuuint64_t)cols, 8, 2, 64, 2}, gs[4] = {4 * rb, rb, 32 * rb, 2 * rb};
  cuuint32_t bd[5] = {(cuuint32_t)bc, 8, 2, (cuuint32_t)bw, 2}, es[5] = {1, 1, 1, 1, 1};
  enc(m, esz == 2 ? CU_TENSOR_MAP_DATA_TYPE_BFLOAT16 : CU_TENSOR_MAP_DATA_TYPE_FLOAT32, 5, (void*)p, gd, gs, bd, es, CU_TENSOR_MAP_INTERLEAVE_NONE,
      swz ? CU_TENSOR_MAP_SWIZZLE_128B : CU_TENSOR_MAP_SWIZZLE_NONE, CU_TENSOR_MAP_L2_PROMOTION_L2_128B, CU_TENSOR_MAP_FLOAT_OOB_FILL_NONE);
}

extern "C" void kernel_launch(void* const* d_in, const int* in_sizes, int n_in, void* d_out, int out_size) {
  (void)in_sizes; (void)n_in; (void)out_size;
  static EncFn enc = nullptr;
  static void *pW, *pwo, *ph, *po;
  if (!enc) {
    void* fn = nullptr; cudaDriverEntryPointQueryResult qr;
    cudaGetDriverEntryPoint("cuTensorMapEncodeTiled", &fn, cudaEnableDefault, &qr);
    enc = (EncFn)fn;
    cudaFuncSetAttribute(fused_kernel, cudaFuncAttributeMaxDynamicSharedMemorySize, SMEM_BYTES);
    cudaGetSymbolAddress(&pW, g_W); cudaGetSymbolAddress(&pwo, g_woT); cudaGetSymbolAddress(&ph, g_h); cudaGetSymbolAddress(&po, g_o);
  }
  Maps M;
  mk5(enc, &M.xB, d_in[4], 2, 576, 64, 4, true);
  mk2(enc, &M.Bre, d_in[7], 2, 576, 576, 64, 72, true);
  mk2(enc, &M.Bim, d_in[8], 2, 576, 576, 64, 72, true);
  mk2(enc, &M.xA, d_in[0], 2, 576, 2048, 64, 128, true);
  mk2(enc, &M.W, pW, 2, 576, 1728, 64, 72, true);
  mk2(enc, &M.hL, ph, 2, 1152, 2048, 64, 128, true);
  mk2(enc, &M.Cre, d_in[9], 2, 576, 576, 64, 72, true);
  mk2(enc, &M.Cim, d_in[10], 2, 576, 576, 64, 72, true);
  mk2(enc, &M.oL, po, 2, 576, 2048, 64, 128, true);
  mk2(enc, &M.woT, pwo, 2, 576, 576, 64, 72, true);
  mk2(enc, &M.hS, ph, 2, 1152, 2048, 72, 16, false);
  mk2(enc, &M.oS, po, 2, 576, 2048, 72, 16, false);
  mk5(enc, &M.yS, d_out, 4, 1152, 72, 1, false);
  mk2(enc, &M.aS, d_out, 4, 1152, 2048, 72, 16, false);
  Ptrs P;
  P.wqkv = (const bf16*)d_in[1]; P.wphi = (const bf16*)d_in[2]; P.wo = (const bf16*)d_in[3]; P.xB = (const bf16*)d_in[4];
  P.lre = (const bf16*)d_in[5]; P.lim = (const bf16*)d_in[6]; P.ldt = (const bf16*)d_in[11]; P.dskip = (const bf16*)d_in[12];
  fused_kernel<<<132, 384, SMEM_BYTES, cudaStreamPerThread>>>(M, P);
}
```

```cpp
#include <cuda_runtime.h>
#include <cuda.h>
#include <cuda_bf16.h>
#include <stdint.h>
#include <stddef.h>

typedef __nv_bfloat16 bf16;
typedef unsigned long long u64;
#define G5O 0
#define CK2 1
#define YG 5
#define YI 1
#define F2 0
#define F3 2
#define RP 0
#define W1 3
#define W2 4
#define GATE 0
#define GJ 2
#define GN 16
#define ONC 0
#define OF 0
#define RH 2
#define XH 41
#define NOX 0
#define PTS 0
#define LDS_ 2
#define CH 12
#define CW 3
#define FW 0
#define KR 3
#define PAUSE 0
#define SKV 0
#define PF 0

template <int TA, int TB> __device__ __forceinline__ void wg_ss144(float (&d)[72], uint64_t da, uint64_t db, int scaleD) {
  asm volatile("{\n.reg .pred p;\nsetp.ne.b32 p, %74, 0;\n"
    "wgmma.mma_async.sync.aligned.m64n144k16.f32.bf16.bf16 {%0, %1, %2, %3, %4, %5, %6, %7, %8, %9, %10, %11, %12, %13, %14, %15, %16, %17, %18, %19, %20, %21, %22, %23, %24, %25, %26, %27, %28, %29, %30, %31, %32, %33, %34, %35, %36, %37, %38, %39, %40, %41, %42, %43, %44, %45, %46, %47, %48, %49, %50, %51, %52, %53, %54, %55, %56, %57, %58, %59, %60, %61, %62, %63, %64, %65, %66, %67, %68, %69, %70, %71}, %72, %73, p, 1, 1, %75, %76;\n}"
    : "+f"(d[0]), "+f"(d[1]), "+f"(d[2]), "+f"(d[3]), "+f"(d[4]), "+f"(d[5]), "+f"(d[6]), "+f"(d[7]), "+f"(d[8]), "+f"(d[9]), "+f"(d[10]), "+f"(d[11]), "+f"(d[12]), "+f"(d[13]), "+f"(d[14]), "+f"(d[15]), "+f"(d[16]), "+f"(d[17]), "+f"(d[18]), "+f"(d[19]), "+f"(d[20]), "+f"(d[21]), "+f"(d[22]), "+f"(d[23]), "+f"(d[24]), "+f"(d[25]), "+f"(d[26]), "+f"(d[27]), "+f"(d[28]), "+f"(d[29]), "+f"(d[30]), "+f"(d[31]), "+f"(d[32]), "+f"(d[33]), "+f"(d[34]), "+f"(d[35]), "+f"(d[36]), "+f"(d[37]), "+f"(d[38]), "+f"(d[39]), "+f"(d[40]), "+f"(d[41]), "+f"(d[42]), "+f"(d[43]), "+f"(d[44]), "+f"(d[45]), "+f"(d[46]), "+f"(d[47]), "+f"(d[48]), "+f"(d[49]), "+f"(d[50]), "+f"(d[51]), "+f"(d[52]), "+f"(d[53]), "+f"(d[54]), "+f"(d[55]), "+f"(d[56]), "+f"(d[57]), "+f"(d[58]), "+f"(d[59]), "+f"(d[60]), "+f"(d[61]), "+f"(d[62]), "+f"(d[63]), "+f"(d[64]), "+f"(d[65]), "+f"(d[66]), "+f"(d[67]), "+f"(d[68]), "+f"(d[69]), "+f"(d[70]), "+f"(d[71])
    : "l"(da), "l"(db), "r"(scaleD), "n"(TA), "n"(TB));
}
template <int TA, int TB> __device__ __forceinline__ void wg_ss24(float (&d)[12], uint64_t da, uint64_t db, int scaleD) {
  asm volatile("{\n.reg .pred p;\nsetp.ne.b32 p, %14, 0;\n"
    "wgmma.mma_async.sync.aligned.m64n24k16.f32.bf16.bf16 {%0, %1, %2, %3, %4, %5, %6, %7, %8, %9, %10, %11}, %12, %13, p, 1, 1, %15, %16;\n}"
    : "+f"(d[0]), "+f"(d[1]), "+f"(d[2]), "+f"(d[3]), "+f"(d[4]), "+f"(d[5]), "+f"(d[6]), "+f"(d[7]), "+f"(d[8]), "+f"(d[9]), "+f"(d[10]), "+f"(d[11])
    : "l"(da), "l"(db), "r"(scaleD), "n"(TA), "n"(TB));
}
__device__ __forceinline__ void wg_rs72(float (&d)[36], uint32_t a0, uint32_t a1, uint32_t a2, uint32_t a3, uint64_t db, int scaleD) {
  asm volatile("{\n.reg .pred p;\nsetp.ne.b32 p, %41, 0;\n"
    "wgmma.mma_async.sync.aligned.m64n72k16.f32.bf16.bf16 {%0, %1, %2, %3, %4, %5, %6, %7, %8, %9, %10, %11, %12, %13, %14, %15, %16, %17, %18, %19, %20, %21, %22, %23, %24, %25, %26, %27, %28, %29, %30, %31, %32, %33, %34, %35}, {%36,%37,%38,%39}, %40, p, 1, 1, 1;\n}"
    : "+f"(d[0]), "+f"(d[1]), "+f"(d[2]), "+f"(d[3]), "+f"(d[4]), "+f"(d[5]), "+f"(d[6]), "+f"(d[7]), "+f"(d[8]), "+f"(d[9]), "+f"(d[10]), "+f"(d[11]), "+f"(d[12]), "+f"(d[13]), "+f"(d[14]), "+f"(d[15]), "+f"(d[16]), "+f"(d[17]), "+f"(d[18]), "+f"(d[19]), "+f"(d[20]), "+f"(d[21]), "+f"(d[22]), "+f"(d[23]), "+f"(d[24]), "+f"(d[25]), "+f"(d[26]), "+f"(d[27]), "+f"(d[28]), "+f"(d[29]), "+f"(d[30]), "+f"(d[31]), "+f"(d[32]), "+f"(d[33]), "+f"(d[34]), "+f"(d[35])
    : "r"(a0), "r"(a1), "r"(a2), "r"(a3), "l"(db), "r"(scaleD));
}
__device__ __forceinline__ void wg_rs80(float (&d)[40], uint32_t a0, uint32_t a1, uint32_t a2, uint32_t a3, uint64_t db, int scaleD) {
  asm volatile("{\n.reg .pred p;\nsetp.ne.b32 p, %45, 0;\n"
    "wgmma.mma_async.sync.aligned.m64n80k16.f32.bf16.bf16 {%0, %1, %2, %3, %4, %5, %6, %7, %8, %9, %10, %11, %12, %13, %14, %15, %16, %17, %18, %19, %20, %21, %22, %23, %24, %25, %26, %27, %28, %29, %30, %31, %32, %33, %34, %35, %36, %37, %38, %39}, {%40,%41,%42,%43}, %44, p, 1, 1, 1;\n}"
    : "+f"(d[0]), "+f"(d[1]), "+f"(d[2]), "+f"(d[3]), "+f"(d[4]), "+f"(d[5]), "+f"(d[6]), "+f"(d[7]), "+f"(d[8]), "+f"(d[9]), "+f"(d[10]), "+f"(d[11]), "+f"(d[12]), "+f"(d[13]), "+f"(d[14]), "+f"(d[15]), "+f"(d[16]), "+f"(d[17]), "+f"(d[18]), "+f"(d[19]), "+f"(d[20]), "+f"(d[21]), "+f"(d[22]), "+f"(d[23]), "+f"(d[24]), "+f"(d[25]), "+f"(d[26]), "+f"(d[27]), "+f"(d[28]), "+f"(d[29]), "+f"(d[30]), "+f"(d[31]), "+f"(d[32]), "+f"(d[33]), "+f"(d[34]), "+f"(d[35]), "+f"(d[36]), "+f"(d[37]), "+f"(d[38]), "+f"(d[39])
    : "r"(a0), "r"(a1), "r"(a2), "r"(a3), "l"(db), "r"(scaleD));
}

constexpr int SA = 34816, SB = 27648;
constexpr int HC = 1056, HA = 8 * HC;
constexpr int OFF_D   = 5 * SA;
constexpr int D_PHI = 18432, D_F2 = 30720, D_K0 = 38016, D_CS = 40960;
constexpr int OFF_TAB = OFF_D + 52480;
constexpr int OFF_BAR = OFF_TAB + 5 * 576;
constexpr int OFF_TS  = OFF_BAR + 256;
constexpr int SMEM_BYTES = OFF_TS + 512 + 1024;
constexpr int BAR_FULL = 0, BAR_EMPTY = 64, BAR_ZT = 128, BAR_TAB = 136, BAR_LD = 160, BAR_OM = 176, BAR_OD = 192, BAR_KVP = 200, BAR_G3 = 144, BAR_G4 = 152, BAR_W1 = 168, BAR_W2 = 184;
constexpr int TILE_B = 18432;
constexpr int WT_Q = 72, WT_C = 81, WT_WO = 99;
constexpr int CN_KV = 0, CN_ALL = 8, CN_H = 9, CN_G = 25;
constexpr float LOG2E = 1.4426950408889634f;

struct Scratch {
  uint8_t Wt[216 * TILE_B];
  uint8_t h[32 * 144 * HC];
  uint4 o[32 * 4 * 9 * 128];
  uint4 kvp[8 * 16 * 736];
  u64 kvt[8 * 736];
  u64 carry[16 * 576];
  unsigned cnt[41 * 32];
  unsigned epoch[128 * 8];
};
__device__ __align__(1024) Scratch g_scr;

struct Maps { CUtensorMap xB, Bre, Bim, xA, xAh, y, Cre, Cim, Wq; };
struct Ptrs { const bf16 *xA, *bre, *bim, *wqkv, *wphi, *wo, *xB, *lre, *lim, *cre, *cim, *ldt, *dskip; float* out; Scratch* s; };

__device__ __forceinline__ uint32_t smem_u32(const void* p) { return (uint32_t)__cvta_generic_to_shared(p); }
__device__ __forceinline__ void mbar_init(uint32_t bar, int cnt) { asm volatile("mbarrier.init.shared::cta.b64 [%0], %1;" ::"r"(bar), "r"(cnt) : "memory"); }
__device__ __forceinline__ void mbar_expect(uint32_t bar, int bytes) { asm volatile("mbarrier.arrive.expect_tx.shared::cta.b64 _, [%0], %1;" ::"r"(bar), "r"(bytes) : "memory"); }
__device__ __forceinline__ void mbar_arrive(uint32_t bar) { asm volatile("mbarrier.arrive.shared::cta.b64 _, [%0];" ::"r"(bar) : "memory"); }
__device__ __forceinline__ void mbar_wait(uint32_t bar, int parity) {
  asm volatile("{\n.reg .pred p;\n.reg .u32 c;\nmov.u32 c, 0;\nLAB_WAIT:\n"
               "mbarrier.try_wait.parity.shared::cta.b64 p, [%0], %1;\n@p bra DONE;\n"
               "add.u32 c, c, 1;\nsetp.lt.u32 p, c, 0x400000;\n@p bra LAB_WAIT;\ntrap;\nDONE:\n}" ::"r"(bar), "r"(parity) : "memory");
}
__device__ __forceinline__ bool mbar_test(uint32_t bar) {
  uint32_t p; asm volatile("{\n.reg .pred P;\nmbarrier.test_wait.parity.shared::cta.b64 P, [%1], 0;\nselp.u32 %0, 1, 0, P;\n}" : "=r"(p) : "r"(bar) : "memory"); return __any_sync(0xffffffffu, p); }
__device__ __forceinline__ bool elect_one() { uint32_t p; asm volatile("{\n.reg .pred P;\nelect.sync _|P, 0xffffffff;\nselp.u32 %0, 1, 0, P;\n}" : "=r"(p)); return p; }
__device__ __forceinline__ void tma2d(uint32_t dst, const CUtensorMap* tm, uint32_t bar, int x, int y) {
  asm volatile("cp.async.bulk.tensor.2d.shared::cluster.global.mbarrier::complete_tx::bytes [%0], [%1, {%3,%4}], [%2];" ::"r"(dst), "l"(tm), "r"(bar), "r"(x), "r"(y) : "memory"); }
__device__ __forceinline__ void tma5d(uint32_t dst, const CUtensorMap* tm, uint32_t bar, int x, int y) {
  asm volatile("cp.async.bulk.tensor.5d.shared::cluster.global.mbarrier::complete_tx::bytes [%0], [%1, {%3,0,0,%4,0}], [%2];" ::"r"(dst), "l"(tm), "r"(bar), "r"(x), "r"(y) : "memory"); }
__device__ __forceinline__ void bulk_ld(uint32_t dst, const void* src, int bytes, uint32_t bar) {
  asm volatile("cp.async.bulk.shared::cluster.global.mbarrier::complete_tx::bytes [%0], [%1], %2, [%3];" ::"r"(dst), "l"(src), "r"(bytes), "r"(bar) : "memory"); }
__device__ __forceinline__ void pf_l2(const void* p, int bytes) { asm volatile("cp.async.bulk.prefetch.L2.global [%0], %1;" ::"l"(p), "r"(bytes) : "memory"); }
__device__ __forceinline__ void fence_async_smem() { asm volatile("fence.proxy.async.shared::cta;" ::: "memory"); }
__device__ __forceinline__ void pfdesc(const CUtensorMap* tm) { asm volatile("prefetch.tensormap [%0];" ::"l"(tm) : "memory"); }
__device__ __forceinline__ uint64_t desc_sw(uint32_t addr) { return (uint64_t)((addr & 0x3FFFF) >> 4) | ((uint64_t)1 << 16) | ((uint64_t)64 << 32) | ((uint64_t)1 << 62); }
template <int LBO, int SBO> __device__ __forceinline__ uint64_t desc_cm(uint32_t addr) { return (uint64_t)((addr & 0x3FFFF) >> 4) | ((uint64_t)(LBO >> 4) << 16) | ((uint64_t)(SBO >> 4) << 32); }
template <int ID, int N> __device__ __forceinline__ void nb_sync() { asm volatile("bar.sync %0, %1;" ::"n"(ID), "n"(N) : "memory"); }
template <int ID, int N> __device__ __forceinline__ void nb_arrive() { asm volatile("bar.arrive %0, %1;" ::"n"(ID), "n"(N) : "memory"); }
__device__ __forceinline__ void wg_fence() { asm volatile("wgmma.fence.sync.aligned;" ::: "memory"); }
__device__ __forceinline__ void wg_commit() { asm volatile("wgmma.commit_group.sync.aligned;" ::: "memory"); }
template <int N> __device__ __forceinline__ void wg_wait() { asm volatile("wgmma.wait_group.sync.aligned %0;" ::"n"(N) : "memory"); }
template <int N> __device__ __forceinline__ void pin(float (&d)[N]) {
#pragma unroll
  for (int r = 0; r < N; r++) asm volatile("" : "+f"(d[r])::"memory");
}
__device__ __forceinline__ void cnt_add(unsigned* c) { asm volatile("red.release.gpu.global.add.u32 [%0], 1;" ::"l"(c) : "memory"); }
__device__ __forceinline__ void cnt_add_done(unsigned* c) { asm volatile("fence.proxy.async.global;\nred.relaxed.gpu.global.add.u32 [%0], 1;" ::"l"(c) : "memory"); }
__device__ __forceinline__ void bulk_st(void* dst, uint32_t src, int bytes) { asm volatile("cp.async.bulk.global.shared::cta.bulk_group [%0], [%1], %2;" ::"l"(dst), "r"(src), "r"(bytes) : "memory"); }
__device__ __forceinline__ void bulk_commit() { asm volatile("cp.async.bulk.commit_group;" ::: "memory"); }
__device__ __forceinline__ void bulk_wait_read() { asm volatile("cp.async.bulk.wait_group.read 0;" ::: "memory"); }
__device__ __forceinline__ void bulk_wait() { asm volatile("cp.async.bulk.wait_group 0;" ::: "memory"); }
__device__ __forceinline__ void cnt_wait(const unsigned* c, unsigned target) {
#pragma unroll 1
  for (int it = 0; it < (1 << 20); it++) {
    unsigned v; asm volatile("ld.acquire.gpu.global.u32 %0, [%1];" : "=r"(v) : "l"(c) : "memory");
    if ((int)(v - target) >= 0) break;
  }
  asm volatile("fence.proxy.async.global;" ::: "memory");
}
__device__ __forceinline__ uint2 ld_ll(const u64* p) { u64 v; asm volatile("ld.relaxed.gpu.global.u64 %0, [%1];" : "=l"(v) : "l"(p) : "memory"); return make_uint2((uint32_t)v, (uint32_t)(v >> 32)); }
__device__ __forceinline__ void st_ll(u64* p, uint32_t lo, uint32_t hi) { u64 v = ((u64)hi << 32) | lo; asm volatile("st.relaxed.gpu.global.u64 [%0], %1;" ::"l"(p), "l"(v) : "memory"); }
__device__ __forceinline__ uint4 ld_ll16(const uint4* p) {
  u64 a, b; asm volatile("{\n.reg .b128 t;\nld.relaxed.gpu.global.b128 t, [%2];\nmov.b128 {%0,%1}, t;\n}" : "=l"(a), "=l"(b) : "l"(p) : "memory");
  return make_uint4((uint32_t)a, (uint32_t)(a >> 32), (uint32_t)b, (uint32_t)(b >> 32)); }
__device__ __forceinline__ void st_ll16(uint4* p, uint32_t x, uint32_t y, uint32_t z, uint32_t w) {
  const u64 a = ((u64)y << 32) | x, b = ((u64)w << 32) | z;
  asm volatile("{\n.reg .b128 t;\nmov.b128 t, {%1,%2};\nst.relaxed.gpu.global.b128 [%0], t;\n}" ::"l"(p), "l"(a), "l"(b) : "memory"); }
__device__ __forceinline__ uint32_t ld_ll4(const void* p) { uint32_t v; asm volatile("ld.relaxed.gpu.global.u32 %0, [%1];" : "=r"(v) : "l"(p) : "memory"); return v; }
__device__ __forceinline__ void tag_wait(const void* p, uint32_t tag, uint32_t mask) {
#pragma unroll 1
  for (int it = 0; it < (1 << 20); it++) if (!__any_sync(0xffffffffu, (ld_ll4(p) ^ tag) & mask)) break;
}
template <uint32_t MASK> __device__ __forceinline__ void re_ll(uint2& v, const u64* p, uint32_t tag) {
  asm volatile("{\n.reg .pred p;\n.reg .b32 t;\nlop3.b32 t, %0, %3, %4, 0x28;\nsetp.ne.u32 p, t, 0;\n@p ld.relaxed.gpu.global.v2.u32 {%0,%1}, [%2];\n}" : "+r"(v.x), "+r"(v.y) : "l"(p), "r"(tag), "n"(MASK) : "memory"); }
template <uint32_t MASK, int Z> __device__ __forceinline__ void re_ll16(uint4& v, const uint4* p, uint32_t tag) {
  asm volatile("{\n.reg .pred p;\n.reg .b32 t;\nlop3.b32 t, %7, %5, %6, 0x28;\nsetp.ne.u32 p, t, 0;\n@p ld.relaxed.gpu.global.v4.u32 {%0,%1,%2,%3}, [%4];\n}" : "+r"(v.x), "+r"(v.y), "+r"(v.z), "+r"(v.w) : "l"(p), "r"(tag), "n"(MASK), "r"(Z ? v.z : v.x) : "memory"); }
__device__ __forceinline__ void gate_wait(const unsigned* c, unsigned target) {
  uint32_t a = ld_ll4(c); __nanosleep(100); uint32_t b = ld_ll4(c); __nanosleep(100); uint32_t d = ld_ll4(c);
#pragma unroll 1
  for (int it = 0; it < (1 << 19); it++) {
    if ((int)(a - target) >= 0) break; a = ld_ll4(c);
    if ((int)(b - target) >= 0) break; b = ld_ll4(c);
    if ((int)(d - target) >= 0) break; d = ld_ll4(c);
  }
}
__device__ __forceinline__ void gate_add(unsigned* c, int lane) { if (lane < 8) asm volatile("red.relaxed.gpu.global.add.u32 [%0], 1;" ::"l"(c + lane * 32) : "memory"); }
__device__ __forceinline__ uint4 ld_weak16(const uint4* p) { uint4 v; asm volatile("ld.global.L1::no_allocate.v4.u32 {%0,%1,%2,%3}, [%4];" : "=r"(v.x), "=r"(v.y), "=r"(v.z), "=r"(v.w) : "l"(p) : "memory"); return v; }
__device__ __forceinline__ uint32_t orx(uint32_t acc, uint32_t x, uint32_t t) { uint32_t r; asm("lop3.b32 %0, %1, %2, %3, 0xf6;" : "=r"(r) : "r"(acc), "r"(x), "r"(t)); return r; }
__device__ __forceinline__ uint32_t tagf(float v, uint32_t tag) { return (__float_as_uint(v) & ~255u) | tag; }
__device__ __forceinline__ uint32_t pack(float lo, float hi) { uint32_t r; asm("cvt.rn.bf16x2.f32 %0, %1, %2;" : "=r"(r) : "f"(hi), "f"(lo)); return r; }
__device__ __forceinline__ float lo16(uint32_t v) { return __uint_as_float(v << 16); }
__device__ __forceinline__ float hi16(uint32_t v) { return __uint_as_float(v & 0xffff0000u); }
__device__ __forceinline__ float ex2(float x) { float r; asm volatile("ex2.approx.ftz.f32 %0, %1;" : "=f"(r) : "f"(x)); return r; }
__device__ __forceinline__ float rcp(float x) { float r; asm("rcp.approx.ftz.f32 %0, %1;" : "=f"(r) : "f"(x)); return r; }
__device__ __forceinline__ void sts128(uint32_t a, uint32_t x, uint32_t y, uint32_t z, uint32_t w) { asm volatile("st.shared.v4.u32 [%0], {%1,%2,%3,%4};" ::"r"(a), "r"(x), "r"(y), "r"(z), "r"(w) : "memory"); }
__device__ __forceinline__ void sts128f(uint32_t a, float x, float y, float z, float w) { asm volatile("st.shared.v4.f32 [%0], {%1,%2,%3,%4};" ::"r"(a), "f"(x), "f"(y), "f"(z), "f"(w) : "memory"); }
__device__ __forceinline__ void sts64f(uint32_t a, float x, float y) { asm volatile("st.shared.v2.f32 [%0], {%1,%2};" ::"r"(a), "f"(x), "f"(y) : "memory"); }
__device__ __forceinline__ void sts32(uint32_t a, uint32_t x) { asm volatile("st.shared.u32 [%0], %1;" ::"r"(a), "r"(x) : "memory"); }
__device__ __forceinline__ float4 lds128f(uint32_t a) { float4 v; asm volatile("ld.shared.v4.f32 {%0,%1,%2,%3}, [%4];" : "=f"(v.x), "=f"(v.y), "=f"(v.z), "=f"(v.w) : "r"(a) : "memory"); return v; }
__device__ __forceinline__ uint4 lds128(uint32_t a) { uint4 v; asm volatile("ld.shared.v4.u32 {%0,%1,%2,%3}, [%4];" : "=r"(v.x), "=r"(v.y), "=r"(v.z), "=r"(v.w) : "r"(a) : "memory"); return v; }
__device__ __forceinline__ uint32_t lds32(uint32_t a) { uint32_t v; asm volatile("ld.shared.u32 %0, [%1];" : "=r"(v) : "r"(a) : "memory"); return v; }
__device__ __forceinline__ float2 lds64f(uint32_t a) { float2 v; asm volatile("ld.shared.v2.f32 {%0,%1}, [%2];" : "=f"(v.x), "=f"(v.y) : "r"(a) : "memory"); return v; }
__device__ __forceinline__ uint32_t ldg32(const void* p) { uint32_t v; asm volatile("ld.global.nc.u32 %0, [%1];" : "=r"(v) : "l"(p)); return v; }
__device__ __forceinline__ uint32_t ldg16(const void* p) { uint32_t v; asm volatile("ld.global.nc.u16 %0, [%1];" : "=r"(v) : "l"(p)); return v; }
__device__ __forceinline__ uint2 ldg64(const void* p) { uint2 v; asm volatile("ld.global.nc.v2.u32 {%0,%1}, [%2];" : "=r"(v.x), "=r"(v.y) : "l"(p)); return v; }
__device__ __forceinline__ uint4 ldg128(const void* p) { uint4 v; asm volatile("ld.global.nc.v4.u32 {%0,%1,%2,%3}, [%4];" : "=r"(v.x), "=r"(v.y), "=r"(v.z), "=r"(v.w) : "l"(p)); return v; }
__device__ __forceinline__ uint32_t vmov(uint32_t x) { uint32_t r; asm volatile("mov.b32 %0, %1;" : "=r"(r) : "r"(x)); return r; }
__device__ __forceinline__ uint4 vmov(uint4 x) { return make_uint4(vmov(x.x), vmov(x.y), vmov(x.z), vmov(x.w)); }
__device__ __forceinline__ void stg32(void* p, uint32_t x) { *(uint32_t*)p = x; }
__device__ __forceinline__ void stg64(void* p, uint32_t x, uint32_t y) { *(uint2*)p = make_uint2(x, y); }
__device__ __forceinline__ void stg128(void* p, uint32_t x, uint32_t y, uint32_t z, uint32_t w) { *(uint4*)p = make_uint4(x, y, z, w); }
#define TS(i)

template <int MT, int ASW, int BSW, int TB, int N0, int NK, int ORD, int FIRST = 1, int LAST = 1, class F>
__device__ __forceinline__ void mainloop(float (&acc)[MT][72], uint32_t base, F hook) {
  constexpr int SS = MT == 2 ? SA : SB, NS = MT == 2 ? 5 : 6, BOFF = MT == 2 ? 16384 : HA, KA = ASW ? 2 : HC / 8, KB = BSW ? 2 : TB ? 16 : 288;
  uint32_t sa = base + (MT == 2 ? N0 % 5 : (N0 + 4) % 6) * SS;
  const uint32_t fb = base + OFF_BAR + BAR_FULL, eb = base + OFF_BAR + BAR_EMPTY;
#pragma unroll 1
  for (uint32_t n = N0; n < N0 + NK; n++) {
    mbar_wait(fb + 8 * (n & 7), (n >> 3) & 1);
    const uint64_t da = ASW ? desc_sw(sa) : desc_cm<HC, 128>(sa), db = BSW ? desc_sw(sa + BOFF) : TB ? desc_cm<128, 1024>(sa + BOFF) : desc_cm<2304, 128>(sa + BOFF);
    wg_fence();
#pragma unroll
    for (int k = 0; k < 4; k++)
#pragma unroll
      for (int m = 0; m < MT; m++) wg_ss144<0, TB>(acc[m], da + 512 * m + k * KA, db + k * KB, (!FIRST || n > N0 || k > 0));
    wg_commit();
    if (ORD && n == N0 + NK - 1) nb_arrive<ORD, 256>();
    hook(n);
    wg_wait<1>();
    if ((!FIRST || n > N0) && (threadIdx.x & 127) == 0) mbar_arrive(eb + 8 * ((n - 1) & 7));
    sa += SS; if (sa == base + NS * SS) sa = base;
  }
  if (!LAST) return;
  wg_wait<0>();
  if (N0 + NK < 54 && (threadIdx.x & 127) == 0) mbar_arrive(eb + 8 * ((N0 + NK - 1) & 7));
#pragma unroll
  for (int m = 0; m < MT; m++) pin(acc[m]);
}

struct Sm { float a[18], b[18], sa, sb; };
__device__ __forceinline__ void sm_exp(const float (&p)[18], Sm& e) {
#pragma unroll
  for (int f = 0; f < 18; f++) { e.a[f] = ex2(p[f]); e.b[f] = ex2(-p[f]); }
  float sa0 = e.a[0], sa1 = e.a[1], sb0 = e.b[0], sb1 = e.b[1];
#pragma unroll
  for (int f = 2; f < 18; f += 2) { sa0 += e.a[f]; sa1 += e.a[f + 1]; sb0 += e.b[f]; sb1 += e.b[f + 1]; }
  e.sa = sa0 + sa1; e.sb = sb0 + sb1;
  if (__builtin_expect(__any_sync(0xffffffffu, !(e.sa + e.sb <= 1e30f)), 0)) {
    __align__(16) float t[40];
#pragma unroll
    for (int f = 0; f < 18; f++) t[f] = p[f];
    float mx = p[0], mn = p[0];
#pragma unroll 1
    for (int f = 1; f < 18; f++) { mx = fmaxf(mx, t[f]); mn = fminf(mn, t[f]); }
    e.sa = 0.f; e.sb = 0.f;
#pragma unroll 1
    for (int f = 0; f < 18; f++) { const float x = t[f], u = ex2(x - mx), v = ex2(mn - x); t[f] = u; t[20 + f] = v; e.sa += u; e.sb += v; }
#pragma unroll
    for (int f = 0; f < 18; f++) { e.a[f] = t[f]; e.b[f] = t[20 + f]; }
  }
}
__device__ __forceinline__ void sm_norm(const Sm& e, uint32_t (&w)[18]) {
  const float ra = rcp(e.sa), rb = rcp(e.sb);
#pragma unroll
  for (int f = 0; f < 9; f++) { w[f] = pack(e.a[2 * f] * ra, e.a[2 * f + 1] * ra); w[9 + f] = pack(e.b[2 * f] * rb, e.b[2 * f + 1] * rb); }
}

struct Ld { uint4 a0, b0, a1, b1; uint32_t t0, t1; };
__device__ __forceinline__ Ld vmov(const Ld& x) { return Ld{vmov(x.a0), vmov(x.b0), vmov(x.a1), vmov(x.b1), vmov(x.t0), vmov(x.t1)}; }

__global__ void __launch_bounds__(384, 1) fused_kernel(const __grid_constant__ Maps M, const __grid_constant__ Ptrs P) {
  extern __shared__ __align__(1024) uint8_t smem_raw[];
  uint32_t base = (smem_u32(smem_raw) + 1023) & ~1023u;
  asm volatile("mov.u32 %0, %0;" : "+r"(base));
  const int cta = blockIdx.x, tile = (cta >> 3) & 15, grp = cta & 7;
  const int ht = 2 * tile + (grp & 1), cb = grp >> 1;
  const int warp = __shfl_sync(0xffffffffu, threadIdx.x >> 5, 0), lane = threadIdx.x & 31;
  const uint32_t bars = base + OFF_BAR;
  const int tid = threadIdx.x & 127, w = warp & 3, g = lane >> 2, q = lane & 3;
  auto load = [&](const bf16* p0, const bf16* p1, Ld& L) {
    L.a0 = ldg128(p0); L.b0 = ldg128(p0 + 8); L.t0 = ldg32(p0 + 64 - 14 * q);
    L.a1 = ldg128(p1); L.b1 = ldg128(p1 + 8); L.t1 = ldg32(p1 + 64 - 14 * q);
  };
  const bf16* wrow = P.wqkv + (16 * w + g) * 1728 + 72 * grp;
  auto ldw = [&](int i, Ld& L) {
    const int S = 4 * i + w, sl = (S * 57) >> 9, m0 = 4 * (S - 9 * sl) + (g & 1), r = 144 * ((cb + sl) & 3) + 18 * (g >> 1) + m0;
    const bf16* p = P.wo + 72 * grp + 16 * q;
    load(p + (r + (m0 < 18 ? 0 : 54)) * 576, p + (r + (m0 < 16 ? 2 : 56)) * 576, L);
  };
  Ld la; uint32_t wv[9];
  const bf16* pk = wrow + 64 * 1728 * tile + 16 * q;
  if ((warp & 12) == 4) {
    if (tile < 9 && tid < 72) {
#pragma unroll
      for (int j = 0; j < 9; j++) wv[j] = ldg32(P.wphi + (grp * 72 + tid) * 18 + 2 * j);
    }
    const bf16* p = pk + (tile < 9 ? 576 : 1152 - 9 * 64 * 1728);
    load(p, p + 8 * 1728, la);
  }
  unsigned ep;
  if (warp < 8) {
    asm volatile("ld.relaxed.gpu.global.u32 %0, [%1];" : "=r"(ep) : "l"(&P.s->epoch[cta * 8]) : "memory");
    nb_sync<0, 384>();
    const uint32_t Dp = base + OFF_D, tab = base + OFF_TAB;
    asm volatile("setmaxnreg.inc.sync.aligned.u32 232;");
    if (warp < 4) {
      {
        float acc[2][72];
        if (tid < 72) st_ll(&P.s->carry[tile * 576 + grp * 72 + tid], ep, ep);
        mainloop<2, 1, 1, 0, 0, 9, 1>(acc, base, [](uint32_t) {});
        TS(13);
        mbar_wait(bars + BAR_TAB, 0); mbar_wait(bars + BAR_W1, 0);
#pragma unroll
        for (int j = 0; j < 9; j++) {
          const float4 L = lds128f(tab + (8 * j + 2 * q) * 8);
          float t[4];
#pragma unroll
          for (int e = 0; e < 2; e++) {
            const float lr = e ? L.z : L.x, li = e ? L.w : L.y;
            float tr = acc[0][4 * j + e], ti = acc[0][4 * (j + 9) + e];
#pragma unroll
            for (int s = 1; s < 4; s++) {
              const float ur = acc[s >> 1][4 * j + 2 * (s & 1) + e], ui = acc[s >> 1][4 * (j + 9) + 2 * (s & 1) + e];
              const float nr = fmaf(-li, ti, fmaf(lr, tr, ur)), ni = fmaf(li, tr, fmaf(lr, ti, ui));
              tr = nr; ti = ni;
            }
            t[2 * e] = tr; t[2 * e + 1] = ti;
          }
          sts128f(Dp + (8 * w + g) * 576 + (8 * j + 2 * q) * 8, t[0], t[1], t[2], t[3]);
        }
        nb_sync<8, 128>();
        TS(14);
        if (w < 3) {
          const uint32_t tag = (ep + 1) & 255u;
          const int ch = tid < 72 ? tid : 71;
          float2 W4[4]; uint2 cw[15];
          const u64* cp = &P.s->carry[grp * 72 + ch];
          const float2 L4 = lds64f(tab + 2 * 576 + ch * 8), L32 = lds64f(tab + 3 * 576 + ch * 8), L128 = lds64f(tab + 4 * 576 + ch * 8);
#pragma unroll
          for (int c = 0; c < 4; c++) W4[c] = lds64f(Dp + (8 * c) * 576 + ch * 8);
#pragma unroll
          for (int s = 1; s < 8; s++)
#pragma unroll
            for (int c = 0; c < 4; c++) {
              const float2 t = lds64f(Dp + (8 * c + s) * 576 + ch * 8);
              const float nr = fmaf(-L4.y, W4[c].y, fmaf(L4.x, W4[c].x, t.x)), ni = fmaf(L4.y, W4[c].x, fmaf(L4.x, W4[c].y, t.y));
              W4[c].x = nr; W4[c].y = ni;
            }
          float tr = W4[0].x, ti = W4[0].y;
#pragma unroll
          for (int c = 1; c < 4; c++) { const float nr = fmaf(-L32.y, ti, fmaf(L32.x, tr, W4[c].x)), ni = fmaf(L32.y, tr, fmaf(L32.x, ti, W4[c].y)); tr = nr; ti = ni; }
          st_ll(&P.s->carry[tile * 576 + grp * 72 + ch], tagf(tr, tag), __float_as_uint(ti));
          TS(15);
#pragma unroll
          for (int t = 0; t < 15; t++) cw[t] = make_uint2(t < tile ? ~tag : tag, 0u);
#pragma unroll 1
          for (int it = 0; it < (1 << 20); it++) {
            uint32_t bad = 0;
#pragma unroll
            for (int t = 0; t < 15; t++) re_ll<255u>(cw[t], cp + t * 576, tag);
#pragma unroll
            for (int t = 0; t < 15; t++) bad = orx(bad, cw[t].x, tag);
            if (!__any_sync(0xffffffffu, bad & 255u)) break;
          }
          TS(16);
          float hr = 0.f, hi = 0.f;
#pragma unroll
          for (int t = 0; t < 15; t++) if (t < tile) {
            const float nr = fmaf(-L128.y, hi, fmaf(L128.x, hr, __uint_as_float(cw[t].x))), ni = fmaf(L128.y, hr, fmaf(L128.x, hi, __uint_as_float(cw[t].y)));
            hr = nr; hi = ni;
          }
          float2 Pf[4]; Pf[0] = make_float2(hr, hi);
#pragma unroll
          for (int c = 1; c < 4; c++) Pf[c] = make_float2(fmaf(-L32.y, Pf[c - 1].y, fmaf(L32.x, Pf[c - 1].x, W4[c - 1].x)), fmaf(L32.y, Pf[c - 1].x, fmaf(L32.x, Pf[c - 1].y, W4[c - 1].y)));
#pragma unroll
          for (int s = 0; s < 8; s++)
#pragma unroll
            for (int c = 0; c < 4; c++) {
              const uint32_t a = Dp + (8 * c + s) * 576 + ch * 8;
              const float2 t = lds64f(a);
              sts64f(a, Pf[c].x, Pf[c].y);
              const float nr = fmaf(-L4.y, Pf[c].y, fmaf(L4.x, Pf[c].x, t.x)), ni = fmaf(L4.y, Pf[c].x, fmaf(L4.x, Pf[c].y, t.y));
              Pf[c].x = nr; Pf[c].y = ni;
            }
        }
        nb_sync<8, 128>();
        TS(17);
        float4 Hin[9];
#pragma unroll
        for (int j = 0; j < 9; j++) Hin[j] = lds128f(Dp + (8 * w + g) * 576 + (8 * j + 2 * q) * 8);
        mbar_wait(bars + BAR_W2, 0);
        nb_sync<8, 128>();
        const uint32_t hp = Dp + w * 256 + g * 16;
        uint32_t hw[2][4][2];
#pragma unroll
        for (int j = 0; j < 9; j++) {
          const float4 L = lds128f(tab + (8 * j + 2 * q) * 8), H = Hin[j];
          float r0 = H.x, i0 = H.y, r1 = H.z, i1 = H.w;
#pragma unroll
          for (int s = 0; s < 4; s++) {
            const int ir = 4 * j + 2 * (s & 1), ii = ir + 36;
            const float nr0 = fmaf(-L.y, i0, fmaf(L.x, r0, acc[s >> 1][ir])), ni0 = fmaf(L.y, r0, fmaf(L.x, i0, acc[s >> 1][ii]));
            const float nr1 = fmaf(-L.w, i1, fmaf(L.z, r1, acc[s >> 1][ir + 1])), ni1 = fmaf(L.w, r1, fmaf(L.z, i1, acc[s >> 1][ii + 1]));
            r0 = nr0; i0 = ni0; r1 = nr1; i1 = ni1;
            hw[j & 1][s][0] = pack(r0, r1); hw[j & 1][s][1] = pack(i0, i1);
          }
          if (j & 1) {
#pragma unroll
            for (int s = 0; s < 4; s++)
              sts128(hp + q * HC + (j >> 1) * 4 * HC + (s >> 1) * 18 * HC + (s & 1) * 128, hw[0][s][0], hw[0][s][1], hw[1][s][0], hw[1][s][1]);
            if (j == 1) nb_arrive<5, 160>(); if (j == 3) nb_arrive<7, 160>(); if (j == 5) nb_arrive<10, 160>(); if (j == 7) nb_arrive<13, 160>();
          } else if (j == 8) {
#pragma unroll
            for (int s = 0; s < 4; s++)
              sts64f(hp + (16 + (q >> 1)) * HC + (q & 1) * 8 + (s >> 1) * 18 * HC + (s & 1) * 128, __uint_as_float(hw[0][s][0]), __uint_as_float(hw[0][s][1]));
          }
        }
        nb_arrive<14, 160>();
        TS(18);
      }
      nb_sync<2, 256>();
      TS(43);
      TS(20);
      uint4 of[4][9];
      {
        uint32_t ph[2][2][18];
        const uint32_t e1 = ep + 1;
        {
          float acc[1][72];
          mainloop<1, 1, 0, 1, 18, 9, 3>(acc, base, [](uint32_t) {});
          TS(21);
          const int h = lane >> 3, l7 = lane & 7, wp = w & 1;
          const u64* kp = &P.s->kvt[((grp & 6) + (w >> 1)) * 736 + 184 * h + l7];
          const u64 *ka = kp + 72 * wp, *kb = kp + 144 + 24 * wp, *kc = kp + 160 + 16 * wp;
          uint2 kw[12]; uint4 v[8];
          const uint4* pp = &P.s->kvp[(grp * 16 + (tid & 1) * 8) * 736 + tile * 46 + (tid < 92 ? tid >> 1 : 0)];
#pragma unroll
          for (int r = 0; r < 4; r++) {
            if (r == 3) {
              TS(30);
#pragma unroll
              for (int m = 0; m < 12; m++) kw[m] = (NOX & 2) ? make_uint2(e1, e1) : ld_ll(m < 9 ? ka + 8 * m : m < 11 ? kb + 8 * (m - 9) : kc);
            }
            if (r == 0) {
              if (SKV) mbar_wait(bars + BAR_KVP, 0);
#pragma unroll
              for (int t = 0; t < 8; t++) v[t] = ld_ll16(pp + t * 736);
            }
            float p[18]; Sm e;
#pragma unroll
            for (int f = 0; f < 18; f++) p[f] = acc[0][36 * (r >> 1) + 4 * (f >> 1) + 2 * (r & 1) + (f & 1)];
            sm_exp(p, e); sm_norm(e, ph[r >> 1][r & 1]);
            if (r == 0) {
            TS(47);
#pragma unroll 1
            for (int it = 0; it < (1 << 20); it++) {
              uint32_t bad = 0;
#pragma unroll
              for (int t = 0; t < 8; t++) bad = orx(bad, v[t].x, e1);
              if (!__any_sync(0xffffffffu, bad & 255u)) break;
#pragma unroll
              for (int t = 0; t < 8; t++) re_ll16<255u, 0>(v[t], pp + t * 736, e1);
            }
            float s0 = __uint_as_float(v[0].x), s1 = __uint_as_float(v[0].y), s2 = __uint_as_float(v[0].z), s3 = __uint_as_float(v[0].w);
#pragma unroll
            for (int t = 1; t < 8; t++) { s0 += __uint_as_float(v[t].x); s1 += __uint_as_float(v[t].y); s2 += __uint_as_float(v[t].z); s3 += __uint_as_float(v[t].w); }
            s0 += __shfl_xor_sync(0xffffffffu, s0, 1); s1 += __shfl_xor_sync(0xffffffffu, s1, 1);
            s2 += __shfl_xor_sync(0xffffffffu, s2, 1); s3 += __shfl_xor_sync(0xffffffffu, s3, 1);
            if (tid < 92 && !(tid & 1)) st_ll(&P.s->kvt[grp * 736 + tile * 46 + (tid >> 1)], (pack(s0, s1) & ~1u) | (e1 & 1u), pack(s2, s3));
            TS(29);
          }
          }
          TS(22);
#pragma unroll 1
          for (int it = 0; it < (1 << 20); it++) {
            uint32_t bad = 0;
#pragma unroll
            for (int m = 0; m < 12; m++) bad = orx(bad, kw[m].x, e1);
            if (!__any_sync(0xffffffffu, bad & 1u)) break;
#pragma unroll
            for (int m = 0; m < 12; m++) re_ll<1u>(kw[m], m < 9 ? ka + 8 * m : m < 11 ? kb + 8 * (m - 9) : kc, e1);
          }
          TS(25);
          if (!YG && tid == 0) mbar_arrive(bars + BAR_OM);
          mbar_wait(bars + BAR_ZT, 0);
          const uint32_t T = Dp + (w >> 1) * 23360 + 36 * h;
          const uint32_t a = T + (l7 & 3) * 2336 + (l7 >> 2) * 16 + wp * 1152;
#pragma unroll
          for (int m = 0; m < 9; m++) { sts32(a + m * 128, kw[m].x); sts32(a + 4 * 2336 + m * 128, kw[m].y); }
          const uint32_t b = T + (9 - (l7 & 1)) * 2336 + (l7 >> 2) * 128 + ((l7 >> 1) & 1) * 16;
#pragma unroll
          for (int m = 0; m < 3; m++) {
            const int t = m == 2 ? 2 + 2 * wp : 3 * wp + m;
            const uint32_t o = b + (t >> 1) * 1024 + (t & 1) * 256;
            sts32(o, kw[9 + m].x);
            if (t < 4) sts32(o + 512, kw[9 + m].y);
          }
        }
        fence_async_smem();
        nb_sync<8, 128>();
        TS(23);
        float d[2][40];
        wg_fence();
#pragma unroll
        for (int hq = 0; hq < 2; hq++) {
          const uint64_t db = desc_cm<128, 2336>(Dp + hq * 23360);
#pragma unroll
          for (int s = 0; s < 9; s++) wg_rs80(d[hq], ph[hq][0][2 * s], ph[hq][1][2 * s], ph[hq][0][2 * s + 1], ph[hq][1][2 * s + 1], db + 16 * s, s > 0);
          wg_commit();
        }
        uint32_t o[2][18];
        uint4* op = &P.s->o[(ht * 4 + cb) * 1152 + tid];
#pragma unroll
        for (int hq = 0; hq < 2; hq++) {
          if (hq == 0) wg_wait<1>(); else wg_wait<0>();
          pin(d[hq]);
          if (hq == 1 && lane == 0) mbar_arrive(bars + BAR_OD);
#pragma unroll
          for (int i = 0; i < 2; i++) {
            const float r = rcp(d[hq][36 + 2 * i] + 1e-6f);
#pragma unroll
            for (int j = 0; j < 9; j++) o[i][9 * hq + j] = pack(d[hq][4 * j + 2 * i] * r, d[hq][4 * j + 2 * i + 1] * r);
          }
#pragma unroll
          for (int s = 4 * hq; s < 4 + 5 * hq; s++) {
            of[0][s] = make_uint4((o[0][2 * s] & ~1u) | (e1 & 1u), o[1][2 * s], o[0][2 * s + 1], o[1][2 * s + 1]);
            if (!(NOX & 4)) st_ll16(op + s * 128, of[0][s].x, of[0][s].y, of[0][s].z, of[0][s].w);
          }
        }
        TS(24);
      }
      {
        auto fetch = [&](int j) {
          const uint4* p = &P.s->o[(ht * 4 + ((cb + j) & 3)) * 1152 + tid];
#pragma unroll
          for (int s = 0; s < 9; s++) of[j][s] = (NOX & 4) ? make_uint4(vmov(~ep), vmov(ep), vmov(ep), vmov(ep)) : ONC ? ld_weak16(p + s * 128) : ld_ll16(p + s * 128);
        };
        auto check = [&](int j) {
#pragma unroll 1
          for (int it = 0; it < (1 << 20); it++) {
            uint32_t bad = 0;
#pragma unroll
            for (int s = 0; s < 9; s++) bad = orx(bad, of[j][s].x, ~ep);
            if (!__any_sync(0xffffffffu, bad & 1u)) break;
            const uint4* p = &P.s->o[(ht * 4 + ((cb + j) & 3)) * 1152 + tid];
#pragma unroll
            for (int s = 0; s < 9; s++) re_ll16<1u, 0>(of[j][s], p + s * 128, ~ep);
          }
        };
        fetch(1);
        if (F2 < 0) fetch(2);
        TS(48);
        nb_sync<4, 256>();
        TS(26);
        float acc[2][36];
        float* op = P.out + (size_t)(ht * 64 + 16 * w + g) * 1152 + cb * 144;
        auto store = [&](int u) {
#pragma unroll
          for (int i = 0; i < 2; i++) {
#pragma unroll
            for (int m = 0; m < 4; m++) {
              const int r = 8 * m + 2 * i;
              *(float4*)(op + i * 9216 + 72 * u + 16 * m + 4 * q) = make_float4(acc[u][r], acc[u][r + 1], acc[u][r + 4], acc[u][r + 5]);
            }
            *(float2*)(op + i * 9216 + 72 * u + 64 + 2 * q) = make_float2(acc[u][32 + 2 * i], acc[u][33 + 2 * i]);
          }
        };
#pragma unroll
        for (int st = 0; st < 9; st++) {
          const int n = 45 + st;
          if (st == 2) { TS(49); check(1); TS(50); }
          if (st == 4 && !CK2) { TS(51); check(2); TS(52); }
          if (st == (G5O ? 6 : 5)) { if (CK2) TS(52); check(3); TS(53); }
          if (YG && st == YG - 1 && tid == 0) mbar_arrive(bars + BAR_OM);
          mbar_wait(bars + BAR_FULL + 8 * (n & 7), (n >> 3) & 1);
          const uint64_t db = desc_cm<1152, 128>(base + ((n + 4) % 6) * SB + HA);
          wg_fence();
#pragma unroll
          for (int k = 0; k < 8; k++) {
            const int it = 8 * st + k, u = G5O || it < 36 ? (it / 9) & 1 : (it - 36) / 18, S = G5O || it < 36 ? 9 * (it / 18) + it % 9 : 18 + (it - 36) % 18;
            wg_rs72(acc[u], of[S / 9][S % 9].x, of[S / 9][S % 9].y, of[S / 9][S % 9].z, of[S / 9][S % 9].w, db + 144 * k, S > 0);
            if (it == (G5O ? 62 : 53) || it == 17) wg_commit();
          }
          wg_commit();
          if (st >= 1 && st <= 3) { wg_wait<1>(); if (tid == 0) mbar_arrive(bars + BAR_EMPTY + 8 * ((n - 1) & 7)); }
          if (st == F2) fetch(2);
          if (CK2 && st == F3) { check(2); TS(51); }
          if (st == F3) fetch(3);
          if (RP && st == RP) {
            const uint4* p = &P.s->o[(ht * 4 + ((cb + 2) & 3)) * 1152 + tid];
#pragma unroll
            for (int s = 0; s < 9; s++) re_ll16<1u, 0>(of[2][s], p + s * 128, ~ep);
          }
        }
        wg_wait<(G5O ? 2 : 3)>(); pin(acc[0]);
        TS(19);
        store(0);
        wg_wait<0>(); pin(acc[1]);
        TS(27);
        store(1);
        if (tid == 0) P.s->epoch[cta * 8] = ep + 1;
        TS(28);
      }
    } else {
      Ld lb;
      {
        if (tile < 9) {
#pragma unroll
          for (int i = 0; i < 6; i++) if (i < 5 || tid < 80) sts128(Dp + D_PHI + tid * 16 + i * 2048, 0, 0, 0, 0);
          nb_sync<9, 128>();
          if (tid < 72) {
            const int h = tid / 18;
            const int kx = tid < 64 ? 16 * ((tid >> 2) & 3) + 8 * ((tid >> 1) & 1) + 2 * (tid >> 4) + (tid & 1) : tid;
            const uint32_t a = Dp + D_PHI + (kx >> 3) * 1152 + (kx & 7) * 16 + 4 * h;
#pragma unroll
            for (int j = 0; j < 9; j++) sts32(a + j * 128, wv[j]);
          }
          fence_async_smem();
          nb_sync<9, 128>();
        }
        TS(31);
        auto raw = [&](Ld& L) {
          const uint32_t sq = Dp + D_F2 + (16 * w + g) * 144;
          L.a0 = lds128(sq + 32 * q); L.b0 = lds128(sq + 32 * q + 16); L.t0 = lds32(sq + 128 + 4 * q);
          L.a1 = lds128(sq + 1152 + 32 * q); L.b1 = lds128(sq + 1168 + 32 * q); L.t1 = lds32(sq + 1280 + 4 * q);
        };
        auto fold = [&](const Ld& cur, uint32_t dst) {
            float c[36];
            const uint64_t db = desc_cm<1152, 128>(Dp + D_PHI);
            wg_fence();
            wg_rs72(c, cur.a0.x, cur.a1.x, cur.a0.y, cur.a1.y, db, 0);
            wg_rs72(c, cur.a0.z, cur.a1.z, cur.a0.w, cur.a1.w, db + 144, 1);
            wg_rs72(c, cur.b0.x, cur.b1.x, cur.b0.y, cur.b1.y, db + 288, 1);
            wg_rs72(c, cur.b0.z, cur.b1.z, cur.b0.w, cur.b1.w, db + 432, 1);
            wg_rs72(c, cur.t0, cur.t1, 0u, 0u, db + 576, 1);
            wg_commit();

            wg_wait<0>(); pin(c);
            const uint32_t dp = dst + w * 256 + (lane & 15) * 16 + (lane >> 4) * 1024;
            uint32_t o[18];
#pragma unroll
            for (int j = 0; j < 18; j++) o[j] = pack(c[2 * j] * LOG2E, c[2 * j + 1] * LOG2E);
#pragma unroll
            for (int j = 0; j < 4; j++) asm volatile("stmatrix.sync.aligned.m8n8.x4.shared.b16 [%0], {%1,%2,%3,%4};" ::"r"(dp + j * 2048), "r"(o[4 * j]), "r"(o[4 * j + 1]), "r"(o[4 * j + 2]), "r"(o[4 * j + 3]) : "memory");
            asm volatile("stmatrix.sync.aligned.m8n8.x2.shared.b16 [%0], {%1,%2};" ::"r"(dp + 8192), "r"(o[16]), "r"(o[17]) : "memory");
        };
        if (tile < 9) {
          fold(la, Dp);
          nb_arrive<11, 160>(); TS(32);
        } else {
          uint32_t o[9];
#pragma unroll
          for (int i = 0; i < 9; i++) { const int x = i < 8 ? 8 * q + i : 32 + q, h = (x * 57) >> 9; o[i] = Dp + w * 256 + g * 16 + (x - 9 * h) * 1024 + 4 * h; }
#pragma unroll 1
          for (int r = 0; r < 2; r++) {
            const uint32_t v0[9] = {la.a0.x, la.a0.y, la.a0.z, la.a0.w, la.b0.x, la.b0.y, la.b0.z, la.b0.w, la.t0};
            const uint32_t v1[9] = {la.a1.x, la.a1.y, la.a1.z, la.a1.w, la.b1.x, la.b1.y, la.b1.z, la.b1.w, la.t1};
#pragma unroll
            for (int i = 0; i < 9; i++) { sts32(o[i], v0[i]); sts32(o[i] + 128, v1[i]); o[i] += 9216; }
            if (tile > 10) break;
            if (r == 0) load(pk + 1152 - 2 * 64 * 1728, pk + 1152 - (2 * 64 - 8) * 1728, la);
          }
          nb_arrive<11, 160>();
          ldw(tile - 9, lb);
        }
        mbar_wait(bars + BAR_TAB, 0);
        float4 cf[9];
#pragma unroll
        for (int i = 0; i < 9; i++) cf[i] = lds128f(tab + 576 + (i < 8 ? 8 * q + i : 32 + q) * 16);
        mbar_wait(bars + BAR_LD, 0);
        Ld lc;
        if (tile == 12 || tile == 13) ldw(tile - 5, lc);
        TS(60);
#pragma unroll 1
        for (int lr = 8 * w + g; lr < 36; lr += 32) {
          const int R = 36 * tile + lr; const uint32_t src = Dp + D_CS + lr * 144;
          const int hb = (R * 911) >> 16, rr = R - 72 * hb, o = rr < 64 ? (rr >> 4) * 256 + (rr & 2) * 64 + (rr & 12) * 8 + (rr & 1) * 16 : 16 * rr;
          uint8_t* dp = P.s->Wt + (WT_C + (hb >> 1) * 36) * TILE_B + grp * 18 * 2304 + (hb & 1) * 1152 + o;
          auto sc = [&](uint32_t re, uint32_t im, int pr, uint32_t& o1, uint32_t& o2) {
            const float4 C = cf[pr];
            const float r0 = lo16(re), r1 = hi16(re), i0 = lo16(im), i1 = hi16(im);
            o1 = pack(fmaf(r0, C.x, -i0 * C.y), fmaf(r1, C.z, -i1 * C.w));
            o2 = pack(fmaf(-r0, C.y, -i0 * C.x), fmaf(-r1, C.w, -i1 * C.z));
          };
          const uint4 a0 = lds128(src + 32 * q), b0 = lds128(src + 32 * q + 16), a1 = lds128(src + 5248 + 32 * q), b1 = lds128(src + 5264 + 32 * q);
          const uint32_t t0 = lds32(src + 128 + 4 * q), t1 = lds32(src + 5376 + 4 * q);
          uint32_t x, y, z, v;
          sc(a0.x, a1.x, 0, x, y);     sc(b0.x, b1.x, 4, z, v); stg128(dp + (4 * q) * 2304, x, y, z, v);
          sc(a0.y, a1.y, 1, x, y); sc(b0.y, b1.y, 5, z, v); stg128(dp + (4 * q + 1) * 2304, x, y, z, v);
          sc(a0.z, a1.z, 2, x, y); sc(b0.z, b1.z, 6, z, v); stg128(dp + (4 * q + 2) * 2304, x, y, z, v);
          sc(a0.w, a1.w, 3, x, y); sc(b0.w, b1.w, 7, z, v); stg128(dp + (4 * q + 3) * 2304, x, y, z, v);
          sc(t0, t1, 8, x, y); stg64(dp + (16 + (q >> 1)) * 2304 + (q & 1) * 8, x, y);
        }
        __syncwarp();
        TS(59);
        if (tile < 9) {
          raw(lb);
          nb_sync<9, 128>();
          fold(lb, Dp + D_F2);
        } else {
#pragma unroll 1
          for (int u = tile;; u += 4) {
            const Ld& cur = lb;
            const bool more = u == 12 || u == 13;
            const int S = 4 * (u - 9) + w;
            uint8_t* dp = P.s->Wt + (WT_WO + cb * 36) * TILE_B + (G5O ? 9 * (grp & 1) + S + 9 * (S / 9) : S < 18 ? 9 * (grp & 1) + S + (S < 9 ? 0 : 9) : 18 + 18 * (grp & 1) + S) * 2304 + g * 16;
            stg128(dp + q * 256, cur.a0.x, cur.a0.z, cur.b0.x, cur.b0.z); stg128(dp + q * 256 + 128, cur.a0.y, cur.a0.w, cur.b0.y, cur.b0.w);
            stg128(dp + 1152 + q * 256, cur.a1.x, cur.a1.z, cur.b1.x, cur.b1.z); stg128(dp + 1152 + q * 256 + 128, cur.a1.y, cur.a1.w, cur.b1.y, cur.b1.w);
            stg32(dp + 1024 + q * 4, cur.t0); stg32(dp + 1152 + 1024 + q * 4, cur.t1);
            if (!more) break;
            lb = lc;
          }
        }
        TS(63);
        nb_arrive<12, 160>();
        TS(33);
      }
      nb_sync<1, 256>();
      TS(34);
        const int tok = tile * 128 + 32 * w + 4 * g + 2 * (grp & 1);
        const bf16* xp = P.xB + (size_t)tok * 576 + cb * 144;
        const bf16* dp = P.dskip + cb * 144;
        uint2 xs[2][2][4], ds[2][4]; uint32_t xt[2][2], dt[2];
      {
        float acc[2][72];
        mainloop<2, 1, 0, 1, 9, 9, 0>(acc, base, [](uint32_t) {});
        TS(35);
        float kv[4][12];
        uint32_t vp[4][9];
#pragma unroll
        for (int r = 0; r < 4; r++)
#pragma unroll
          for (int d = 0; d < 9; d++) { vp[r][d] = pack(acc[r >> 1][36 + 4 * d + 2 * (r & 1)], acc[r >> 1][36 + 4 * d + 2 * (r & 1) + 1]); asm volatile("" : "+r"(vp[r][d])); }
        const uint32_t a = Dp + D_K0 + q * 3616 + w * 128 + g * 16;
        const uint64_t da = desc_cm<128, 512>(Dp + D_K0);
#pragma unroll
        for (int r = 0; r < 4; r++) {
          Sm e; uint32_t ph[18]; float p[18];
#pragma unroll
          for (int f = 0; f < 18; f++) p[f] = acc[r >> 1][4 * (f >> 1) + 2 * (r & 1) + (f & 1)];
          sm_exp(p, e); sm_norm(e, ph);
#pragma unroll
          for (int f = 0; f < 18; f++) asm volatile("" : "+r"(ph[f]));
          if (r) { wg_wait<0>(); nb_sync<9, 128>(); }
          const uint32_t* v = vp[r];
#pragma unroll
          for (int c = 0; c < 4; c++) sts128(a + 512 * c, ph[4 * c], ph[4 * c + 1], ph[4 * c + 2], ph[4 * c + 3]);
          sts128(a + 2048, ph[16], ph[17], 0x00003F80u, v[8]);
          sts128(a + 2560, v[0], v[1], v[2], v[3]); sts128(a + 3072, v[4], v[5], v[6], v[7]);
          TS(54 + r);
          fence_async_smem();
          nb_sync<9, 128>();
          wg_fence();
#pragma unroll
          for (int s = 0; s < 2; s++)
#pragma unroll
            for (int h = 0; h < 4; h++) wg_ss24<1, 1>(kv[h], da + 226 * h + 16 * s, da + 226 * h + 16 * s + 128, r > 0 || s > 0);
          wg_commit();
          if (r == KR) nb_arrive<2, 256>();
        }
        TS(36);
        wg_wait<0>();
#pragma unroll
        for (int h = 0; h < 4; h++) pin(kv[h]);
        nb_arrive<6, 160>();
        const uint32_t tag = (ep + 1) & 255u;
        uint4* pa = &P.s->kvp[(grp * 16 + tile) * 736 + 64 * w + lane];
        uint4* pb = &P.s->kvp[(grp * 16 + tile) * 736 + 144 + 16 * w + 2 * g + q - 2];
        const bool v0 = 16 * w + g < 36, v1 = w < 2;
#pragma unroll
        for (int h = 0; h < 4; h++) {
          if (v0) st_ll16(pa + 184 * h, tagf(kv[h][4], tag), __float_as_uint(kv[h][5]), __float_as_uint(kv[h][8]), __float_as_uint(kv[h][9]));
          if (v1) st_ll16(pa + 184 * h + 32, tagf(kv[h][6], tag), __float_as_uint(kv[h][7]), __float_as_uint(kv[h][10]), __float_as_uint(kv[h][11]));
          if (v0 && q >= 2) st_ll16(pb + 184 * h, tagf(kv[h][0], tag), __float_as_uint(kv[h][1]), __float_as_uint(kv[h][2]), __float_as_uint(kv[h][3]));
        }
        TS(37);
      }
      {
        nb_sync<3, 256>();
        TS(39);
        float acc[1][72];
        mainloop<1, 0, 0, 0, 27, 18, 4>(acc, base, [&](uint32_t) {
          if (PAUSE && mbar_test(bars + BAR_OM)) mbar_wait(bars + BAR_OD, 0);
        });
        TS(40);
#pragma unroll
        for (int u = 0; u < 2; u++) {
#pragma unroll
          for (int m = 0; m < 4; m++) { ds[u][m] = ldg64(dp + 72 * u + 16 * m + 4 * q); xs[0][u][m] = ldg64(xp + 72 * u + 16 * m + 4 * q); xs[1][u][m] = ldg64(xp + 576 + 72 * u + 16 * m + 4 * q); }
          dt[u] = ldg32(dp + 72 * u + 64 + 2 * q); xt[0][u] = ldg32(xp + 72 * u + 64 + 2 * q); xt[1][u] = ldg32(xp + 576 + 72 * u + 64 + 2 * q);
        }
        auto mul = [](uint32_t x, uint32_t y) { const __nv_bfloat162 r = __hmul2(*(const __nv_bfloat162*)&x, *(const __nv_bfloat162*)&y); return *(const uint32_t*)&r; };
        mbar_wait(bars + BAR_OD, 0);
        const uint32_t ys = Dp + (8 * w + g) * 576;
#pragma unroll
        for (int i = 0; i < 2; i++) {
#pragma unroll
          for (int u = 0; u < 2; u++) {
#pragma unroll
            for (int m = 0; m < 4; m++) {
              const int r = 36 * u + 8 * m + 2 * i;
              const uint32_t s0 = mul(xs[i][u][m].x, ds[u][m].x), s1 = mul(xs[i][u][m].y, ds[u][m].y);
              sts128f(ys + i * 18432 + 288 * u + 64 * m + 16 * q, acc[0][r] + lo16(s0), acc[0][r + 1] + hi16(s0), acc[0][r + 4] + lo16(s1), acc[0][r + 5] + hi16(s1));
            }
            const uint32_t s = mul(xt[i][u], dt[u]);
            sts64f(ys + i * 18432 + 288 * u + 256 + 8 * q, acc[0][36 * u + 32 + 2 * i] + lo16(s), acc[0][36 * u + 33 + 2 * i] + hi16(s));
          }
          if (i == 0) nb_arrive<11, 160>(); else nb_arrive<12, 160>();
        }
        TS(41);
      }
    }
  } else {
    asm volatile("setmaxnreg.dec.sync.aligned.u32 40;");
    const uint32_t fb = bars + BAR_FULL, eb = bars + BAR_EMPTY;
    auto step = [&](uint32_t c, uint32_t f, int bytes, uint32_t win) {
      mbar_wait(eb + (c & 56), (c >> 6) & 1);
      if (win < 5) { const uint32_t e = f - 8 * win; mbar_wait(fb + (e & 56), (e >> 6) & 1); }
      mbar_expect(fb + (f & 56), bytes);
    };
    int role = warp - 8;
    asm volatile("" : "+r"(role));
    if (role > 0) {
    uint32_t tb[6];
    if (warp >= 10) {
      const int c = grp * 72 + threadIdx.x - 320, c2 = c + (threadIdx.x < 328 ? 64 : 0);
      tb[0] = ldg16(P.lre + c); tb[1] = ldg16(P.lim + c); tb[2] = ldg16(P.ldt + c);
      tb[3] = ldg16(P.lre + c2); tb[4] = ldg16(P.lim + c2); tb[5] = ldg16(P.ldt + c2);
    }
    if (elect_one()) {
      if (warp == 9) { mbar_init(bars + BAR_LD, 1); mbar_init(bars + BAR_OM, 1); mbar_init(bars + BAR_OD, 4); mbar_init(bars + BAR_KVP, 1); mbar_init(bars + BAR_ZT, 32); mbar_init(bars + BAR_TAB, 64); }
      else { mbar_init(bars + (warp == 10 ? BAR_G3 : BAR_G4), warp == 10 ? 32 : 1); mbar_init(bars + (warp == 10 ? BAR_W1 : BAR_W2), 1); }
      asm volatile("fence.mbarrier_init.release.cluster;" ::: "memory");
    }
    asm volatile("ld.relaxed.gpu.global.u32 %0, [%1];" : "=r"(ep) : "l"(&P.s->epoch[cta * 8]) : "memory");
    nb_sync<0, 384>();
    if (warp == 9) {
    if (PF) {
      mbar_wait(fb, 0);
      if (lane < 3) pf_l2((lane == 0 ? P.cre : lane == 1 ? P.cim : P.wo) + cta * 2592, 5184);
      else if (lane < 8 && cta * 5 + lane < 579) pf_l2(P.wqkv + (cta * 5 + lane - 3) * 1728, 1152);
    }
      if (elect_one()) {
        const uint8_t* src = P.s->Wt + grp * 9 * TILE_B;
        uint32_t sa = base + 4 * SA + 16384, f = 72;
        mbar_wait(fb + 8 * CW, 0);
        mbar_expect(bars + BAR_LD, tile < 9 ? 19584 : 10368);
        if (tile < 9) tma2d(base + OFF_D + D_F2, &M.Wq, bars + BAR_LD, grp * 72, tile * 64);
        tma2d(base + OFF_D + D_CS, &M.Cre, bars + BAR_LD, grp * 72, tile * 36); tma2d(base + OFF_D + D_CS + 5248, &M.Cim, bars + BAR_LD, grp * 72, tile * 36);
        TS(6);
        cnt_wait(&P.s->cnt[(CN_KV + grp) * 32], (ep + 1) * 16);
        TS(7);
#pragma unroll 1
        for (; f < 144; f += 8) {
          step(f - 40, f, TILE_B, W1); bulk_ld(sa, src, TILE_B, fb + (f & 56));
          if (PTS == 2) TS(64 + f / 8);
          src += TILE_B; sa += SA; if (sa == base + 5 * SA + 16384) sa = base + 16384;
        }
        src = P.s->Wt + (WT_Q + cb * 36) * TILE_B; sa = base + 4 * SB + HA;
        TS(44);
        cnt_wait(&P.s->cnt[(CN_G + cb) * 32], (ep + 1) * 18);
        TS(45);
#pragma unroll 1
        for (; f < 432; f += 8) {
          if (f == 216) { mbar_wait(bars + BAR_G4, 0); asm volatile("fence.proxy.async.global;" ::: "memory"); }
          step(f - (f < 184 ? 40 : 48), f, TILE_B, W2); bulk_ld(sa, src, TILE_B, fb + (f & 56));
          if (f >= 360) mbar_arrive(fb + (f & 56));
          if (PTS == 2) TS(64 + f / 8);
          src += TILE_B; sa += SB; if (sa == base + 6 * SB + HA) sa = base + HA;
        }
        TS(5);
      }
    } else {
      const uint32_t tab = base + OFF_TAB;
#pragma unroll 1
      for (int c = threadIdx.x - 320; c < 72; c += 64) {
        const float lre = lo16(tb[0]), lim = lo16(tb[1]);
        const float dt = __bfloat162float(__float2bfloat16(expf(lo16(tb[2]))));
        tb[0] = tb[3]; tb[1] = tb[4]; tb[2] = tb[5];
        const float e = expf(dt * lre), x = dt * lim;
        const float k2 = 2.f * rintf(x * 0.15915494309189535f);
        float sn, cs; sincospif(fmaf(x, 0.31830987334251404f, -k2) + x * 1.2841276486597053e-08f, &sn, &cs);
        float lr = e * cs, li = e * sn;
        const float rd = 2.f * rcp(lre * lre + lim * lim), nr = lr - 1.f;
        sts64f(tab + c * 8, lr, li);
        sts64f(tab + 576 + c * 8, (nr * lre + li * lim) * rd, (li * lre - nr * lim) * rd);
#pragma unroll
        for (int s = 1; s <= 7; s++) {
          const float t = lr * lr - li * li; li = 2.f * lr * li; lr = t;
          if (s == 2) sts64f(tab + 2 * 576 + c * 8, lr, li);
          if (s == 5) sts64f(tab + 3 * 576 + c * 8, lr, li);
          if (s == 7) sts64f(tab + 4 * 576 + c * 8, lr, li);
        }
      }
      mbar_arrive(bars + BAR_TAB);
      TS(11);
      if (warp == 10) {
        if (elect_one()) { pfdesc(&M.xA); pfdesc(&M.xAh); }
        if (lane < 23) st_ll16((uint4*)&P.s->kvt[grp * 736 + tile * 46] + lane, ep, ep, ep, ep);
      } else {
        nb_sync<11, 160>();
        if (elect_one()) {
          uint8_t* wk = P.s->Wt + (grp * 9 + tile) * TILE_B - (tile < 9 ? 0 : 9 * TILE_B - 9216);
          fence_async_smem();
          bulk_st(wk, base + OFF_D, 9216);
          if (tile == 9 || tile == 10) bulk_st(wk + 7 * TILE_B, base + OFF_D + 9216, 9216);
          bulk_commit(); TS(62); bulk_wait(); cnt_add_done(&P.s->cnt[(CN_KV + grp) * 32]); mbar_arrive(bars + BAR_W1);
        }
        __syncwarp();
        TS(9);
      }
      if (warp == 11) {
          nb_sync<12, 160>();
          if (elect_one()) {
            if (tile < 9) {
              fence_async_smem(); bulk_st(P.s->Wt + (WT_Q + cb * 36 + tile) * TILE_B + (grp & 1) * 9216, base + OFF_D + D_F2, 9216);
              bulk_commit(); bulk_wait(); cnt_add_done(&P.s->cnt[(CN_G + cb) * 32]);
            }
            mbar_arrive(bars + BAR_W2);
          }
          __syncwarp();
      }
      if (warp == 10) {
        mbar_arrive(bars + BAR_G3);
        uint8_t* hp = P.s->h + (tile * 2 * 144 + grp * 18) * HC;
        uint32_t hs = base + OFF_D;
#pragma unroll 1
        for (int i = 0; i < 5; i++) {
          asm volatile("bar.sync %0, 160;" ::"r"(i == 0 ? 5 : i == 1 ? 7 : i == 2 ? 10 : 10 + i) : "memory");
          if (elect_one()) {
            const int bytes = i < 4 ? 4 * HC : 2 * HC;
            fence_async_smem();
            bulk_st(hp, hs, bytes); bulk_st(hp + 144 * HC, hs + 18 * HC, bytes);
            bulk_commit();
          }
          hp += 4 * HC; hs += 4 * HC;
        }
        if (elect_one()) { bulk_wait(); cnt_add_done(&P.s->cnt[(CN_H + tile) * 32]); }
        __syncwarp();
        TS(8);
        uint32_t a = base + OFF_D + lane * 16;
#pragma unroll 1
        for (int i = 0; i < 92; i++) {
          if (i == D_K0 / 512) nb_sync<6, 160>();
          sts128(a, 0, 0, 0, 0); a += 512;
        }
#pragma unroll
        for (int i = 0; i < 4; i++) sts128(a + i * 512, ep, ep, ep, ep);
        fence_async_smem();
        __syncwarp();
        if (elect_one()) {
#pragma unroll 1
          for (int i = 0; i < 9; i++) bulk_st(&P.s->o[(ht * 4 + cb) * 1152 + i * 128], base + OFF_D + 92 * 512, 2048);
          bulk_commit(); bulk_wait();
          asm volatile("fence.proxy.async.global;" ::: "memory");
        }
        __syncwarp();
        mbar_arrive(bars + BAR_ZT);
        TS(46);
      } else {
        mbar_wait(bars + BAR_G3, 0);
        __syncwarp();
        if (elect_one()) cnt_add(&P.s->cnt[CN_ALL * 32]);
        __syncwarp();
        TS(10);
        gate_wait(&P.s->cnt[CN_ALL * 32], (ep + 1) * 128);
        TS(42);
        gate_wait(&P.s->cnt[(CN_H + tile) * 32], (ep + 1) * 8);
        if (lane == 0) mbar_arrive(bars + BAR_G4);
        if (SKV) tag_wait(&P.s->kvp[(grp * 16 + (lane & 15)) * 736 + tile * 46 + (lane >> 4) * 45], ep + 1, 255u);
        if (lane == 0) mbar_arrive(bars + BAR_KVP);
        TS(61);
        if (elect_one()) pfdesc(&M.y);
#pragma unroll 1
        for (int i = 0; i < 2; i++) {
          asm volatile("bar.sync %0, 160;" ::"r"(11 + i) : "memory");
          if (YG && i == YI) mbar_wait(bars + BAR_OM, 0);
          if (elect_one()) {
            fence_async_smem();
            asm volatile("cp.async.bulk.tensor.3d.global.shared::cta.bulk_group [%0, {%2,%3,%4}], [%1];" ::"l"(&M.y), "r"(base + OFF_D + i * 18432), "r"(576 + cb * 144), "r"(2 * (grp & 1) + i), "r"(tile * 32) : "memory");
            bulk_commit();
          }
        }
        if (elect_one()) bulk_wait();
        TS(58);
      }
    }
    } else {
      TS(38);
      const bool one = elect_one();
      auto g1 = [&](uint32_t sa, uint32_t bar, int k) {
        mbar_arrive(bar);
        tma5d(sa, &M.xB, bar, k, tile * 4);
        tma2d(sa + 16384, &M.Bre, bar, k, grp * 72);
        tma2d(sa + 16384 + 9216, &M.Bim, bar, k, grp * 72);
      };
      if (one) {
        mbar_init(fb, 2);
        asm volatile("fence.mbarrier_init.release.cluster;" ::: "memory");
        mbar_expect(fb, SA); g1(base, fb, 0);
#pragma unroll
        for (int i = 1; i < 16; i++) mbar_init(fb + 8 * i, i < 8 ? 2 : 1);
        asm volatile("fence.mbarrier_init.release.cluster;" ::: "memory");
      }
      __syncwarp();
      nb_arrive<0, 384>();
      TS(1);
      if (one) {
        uint32_t sa = base + SA, f = 8;
#pragma unroll 1
        for (; f < 72; f += 8) {
          if (f >= 40) mbar_wait(eb + f - 40, 0);
          if (f == 8 * LDS_) mbar_wait(fb, 0);
          mbar_expect(fb + (f & 56), SA); g1(sa, fb + (f & 56), f * 8);
          if (PTS == 1) TS(64 + f / 8);
          sa += SA; if (f == 32) sa = base;
        }
        asm volatile("ld.relaxed.gpu.global.u32 %0, [%1];" : "=r"(ep) : "l"(&P.s->epoch[cta * 8]) : "memory");
#pragma unroll 1
        for (; f < 144; f += 8) {
          step(f - 40, f, 16384, W1); tma2d(sa, &M.xA, fb + (f & 56), f * 8 - 576, tile * 128);
          if (PTS == 1) TS(64 + f / 8);
          sa += SA; if (sa == base + 5 * SA) sa = base;
        }
        sa = base + 4 * SB;
#pragma unroll 1
        for (; f < 216; f += 8) {
          step(f - (f < 184 ? 40 : 48), f, 8192, W2); tma2d(sa, &M.xAh, fb + (f & 56), f * 8 - 1152, ht * 64);
          if (PTS == 1) TS(64 + f / 8);
          sa += SB; if (sa == base + 6 * SB) sa = base;
        }
        const uint8_t* src = P.s->h + ht * (144 * HC);
        TS(2);
        mbar_wait(bars + BAR_G4, 0);
        asm volatile("fence.proxy.async.global;" ::: "memory");
        TS(3);
#pragma unroll 1
        for (; f < 360; f += 8) {
          step(f - 48, f, HA, W2); bulk_ld(sa, src, HA, fb + (f & 56));
          if (PTS == 1) TS(64 + f / 8);
          src += HA; sa += SB; if (sa == base + 6 * SB) sa = base;
        }
        TS(4);
      }
    }
  }
}

typedef CUresult (*EncFn)(CUtensorMap*, CUtensorMapDataType, cuuint32_t, void*, const cuuint64_t*, const cuuint64_t*, const cuuint32_t*,
                          const cuuint32_t*, CUtensorMapInterleave, CUtensorMapSwizzle, CUtensorMapL2promotion, CUtensorMapFloatOOBfill);

static void mk2(EncFn enc, CUtensorMap* m, const void* p, int rows, int br, int bc = 64, int cols = 576) {
  cuuint64_t gd[2] = {(cuuint64_t)cols, (cuuint64_t)rows}, gs[1] = {(cuuint64_t)cols * 2};
  cuuint32_t bd[2] = {(cuuint32_t)bc, (cuuint32_t)br}, es[2] = {1, 1};
  enc(m, CU_TENSOR_MAP_DATA_TYPE_BFLOAT16, 2, (void*)p, gd, gs, bd, es, CU_TENSOR_MAP_INTERLEAVE_NONE,
      bc == 64 ? CU_TENSOR_MAP_SWIZZLE_128B : CU_TENSOR_MAP_SWIZZLE_NONE, CU_TENSOR_MAP_L2_PROMOTION_L2_128B, CU_TENSOR_MAP_FLOAT_OOB_FILL_NONE);
}
static void mk5(EncFn enc, CUtensorMap* m, const void* p) {
  const cuuint64_t rb = 1152;
  cuuint64_t gd[5] = {576, 8, 2, 64, 2}, gs[4] = {4 * rb, rb, 32 * rb, 2 * rb};
  cuuint32_t bd[5] = {64, 8, 2, 4, 2}, es[5] = {1, 1, 1, 1, 1};
  enc(m, CU_TENSOR_MAP_DATA_TYPE_BFLOAT16, 5, (void*)p, gd, gs, bd, es, CU_TENSOR_MAP_INTERLEAVE_NONE,
      CU_TENSOR_MAP_SWIZZLE_128B, CU_TENSOR_MAP_L2_PROMOTION_L2_128B, CU_TENSOR_MAP_FLOAT_OOB_FILL_NONE);
}

static void mky(EncFn enc, CUtensorMap* m, void* p) {
  cuuint64_t gd[3] = {1152, 4, 512}, gs[2] = {4608, 4 * 4608};
  cuuint32_t bd[3] = {144, 1, 32}, es[3] = {1, 1, 1};
  enc(m, CU_TENSOR_MAP_DATA_TYPE_FLOAT32, 3, p, gd, gs, bd, es, CU_TENSOR_MAP_INTERLEAVE_NONE,
      CU_TENSOR_MAP_SWIZZLE_NONE, CU_TENSOR_MAP_L2_PROMOTION_NONE, CU_TENSOR_MAP_FLOAT_OOB_FILL_NONE);
}

extern "C" void kernel_launch(void* const* d_in, const int* in_sizes, int n_in, void* d_out, int out_size) {
  (void)in_sizes; (void)n_in; (void)out_size;
  static EncFn enc = nullptr;
  static Scratch* scr = nullptr;
  if (!enc) {
    void* fn = nullptr; cudaDriverEntryPointQueryResult qr;
    cudaGetDriverEntryPoint("cuTensorMapEncodeTiled", &fn, cudaEnableDefault, &qr);
    enc = (EncFn)fn;
    cudaGetSymbolAddress((void**)&scr, g_scr);
    cudaFuncSetAttribute(fused_kernel, cudaFuncAttributeMaxDynamicSharedMemorySize, SMEM_BYTES);
  }
  Maps M;
  mk5(enc, &M.xB, d_in[4]);
  mk2(enc, &M.Bre, d_in[7], 576, 72);
  mk2(enc, &M.Bim, d_in[8], 576, 72);
  mk2(enc, &M.xA, d_in[0], 2048, 128);
  mk2(enc, &M.xAh, d_in[0], 2048, 64);
  mky(enc, &M.y, d_out);
  mk2(enc, &M.Cre, d_in[9], 576, 36, 72);
  mk2(enc, &M.Cim, d_in[10], 576, 36, 72);
  mk2(enc, &M.Wq, d_in[1], 576, 64, 72, 1728);
  Ptrs P;
  P.xA = (const bf16*)d_in[0]; P.bre = (const bf16*)d_in[7]; P.bim = (const bf16*)d_in[8];
  P.wqkv = (const bf16*)d_in[1]; P.wphi = (const bf16*)d_in[2]; P.wo = (const bf16*)d_in[3]; P.xB = (const bf16*)d_in[4];
  P.lre = (const bf16*)d_in[5]; P.lim = (const bf16*)d_in[6]; P.cre = (const bf16*)d_in[9]; P.cim = (const bf16*)d_in[10];
  P.ldt = (const bf16*)d_in[11]; P.dskip = (const bf16*)d_in[12]; P.out = (float*)d_out; P.s = scr;
  fused_kernel<<<128, 384, SMEM_BYTES, cudaStreamPerThread>>>(M, P);
}
```
